```python
import torch

def _softmax(x, axis=-1):
    return torch.softmax(x, dim=axis)
def _gelu(x):
    return torch.nn.functional.gelu(x, approximate="tanh")
def _silu(x):
    return torch.nn.functional.silu(x)
def _sigmoid(x):
    return torch.sigmoid(x)
def _layernorm(x, axis=-1, eps=1e-5):
    m = x.mean(dim=axis, keepdim=True)
    v = x.var(dim=axis, keepdim=True, unbiased=False)
    return (x - m) / torch.sqrt(v + eps)
def _scatter_add(tgt, idx, src, axis=0):
    return tgt.clone().index_add_(axis, idx, src)
def _segment_sum(src, seg, n):
    out = torch.zeros((n,) + src.shape[1:], dtype=src.dtype)
    return out.index_add_(0, seg, src)
def _pad(x, pw):
    flat = tuple(v for pair in reversed(pw) for v in pair)
    return torch.nn.functional.pad(x, flat)

kernel_name = 'parallel_sum__sliding_block_cached__dense_activation_gelu__decode'

def setup_inputs():

    _w = (lambda a: (lambda t: t.to(torch.bfloat16) if t.is_floating_point() else t)(torch.as_tensor(a)))
    def _A_setup():
        B, Sq, D = 2, 1, 512
        Hq, Hkv, Sk, Dh = 32, 32, 16384, 128
        assert Hq % Hkv == 0, (Hq, Hkv)
        return {
            "x": _w((lambda *s: torch.randn(*s, dtype=torch.bfloat16) * 0.05)(B, Sq, D)),
            "k_cache": _w((lambda *s: torch.randn(*s, dtype=torch.bfloat16) * 3.2)(B, Hkv, Sk, Dh)),
            "v_cache": _w((lambda *s: torch.randn(*s, dtype=torch.bfloat16) * 0.8)(B, Hkv, Sk, Dh)),
            "wq": _w((lambda *s: torch.randn(*s, dtype=torch.bfloat16) * 3.2)(D, Hq * Dh) * (D ** -0.5)),
            "wo": _w((lambda *s: torch.randn(*s, dtype=torch.bfloat16) * 0.8)(Hq * Dh, D) * ((Hq * Dh) ** -0.5)),
        }
    _A_in = _A_setup()

    def _B_setup():
        B, S, D, F = 2, 1, 512, 1376
        return {
            "x": _w((lambda *s: torch.randn(*s, dtype=torch.bfloat16) * 0.05)(B, S, D)),
            "w1": _w((lambda *s: torch.randn(*s, dtype=torch.bfloat16) * 3.2)(D, F) * (D ** -0.5)),
            "b1": _w((lambda *s: torch.randn(*s, dtype=torch.bfloat16) * 3.2)(F) * 0.01),
            "w2": _w((lambda *s: torch.randn(*s, dtype=torch.bfloat16) * 0.4)(F, D) * (F ** -0.5)),
            "b2": _w((lambda *s: torch.randn(*s, dtype=torch.bfloat16) * 0.4)(D) * 0.01),
        }
    _B_in = _B_setup()

    return {
        "A_x": _A_in["x"],
        "A_k_cache": _A_in["k_cache"],
        "A_v_cache": _A_in["v_cache"],
        "A_wq": _A_in["wq"],
        "A_wo": _A_in["wo"],
        "B_x": _B_in["x"],
        "B_w1": _B_in["w1"],
        "B_b1": _B_in["b1"],
        "B_w2": _B_in["w2"],
        "B_b2": _B_in["b2"],
    }

def reference(A_x, A_k_cache, A_v_cache, A_wq, A_wo, B_x, B_w1, B_b1, B_w2, B_b2):
    def _A_ref(x, k_cache, v_cache, wq, wo):
        B, Sq, D = x.shape
        Hq, Dh = 32, 128
        Hkv, Sk = k_cache.shape[1], k_cache.shape[2]
        W = min(4096, max(256, Sk // 4))
        rep = Hq // Hkv
        q = (lambda x, *d: x.permute(*d))((x @ wq).reshape(B, Sq, Hq, Dh), 0, 2, 1, 3)
        k = (lambda x, n, axis: torch.repeat_interleave(x, n, dim=axis))(k_cache[:, :, Sk - W:, :], rep, axis=1)
        v = (lambda x, n, axis: torch.repeat_interleave(x, n, dim=axis))(v_cache[:, :, Sk - W:, :], rep, axis=1)
        scores = torch.einsum("bhqd,bhkd->bhqk", q, k) * (Dh ** -0.5)
        p = _softmax(scores, axis=-1)
        o = torch.einsum("bhqk,bhkd->bhqd", p, v)
        return (lambda x, *d: x.permute(*d))(o, 0, 2, 1, 3).reshape(B, Sq, Hq * Dh) @ wo

    def _B_ref(x, w1, b1, w2, b2):
        h = torch.einsum("bsd,df->bsf", x, w1) + b1
        h = _gelu(h)
        return torch.einsum("bsf,fd->bsd", h, w2) + b2

    x = A_x
    xn = _layernorm(x, axis=-1)
    return x + _A_ref(xn, A_k_cache, A_v_cache, A_wq, A_wo) + _B_ref(xn, B_w1, B_b1, B_w2, B_b2)
```

```cpp
#include <cuda_runtime.h>
#include <cuda_bf16.h>
#include <stdint.h>

namespace {

constexpr int DM = 512, NH = 32, SK = 16384, WIN = 4096, DH = 128, FF = 1376;
constexpr int NATT = 128, NFFN = 4, NCTA = NATT + NFFN;
constexpr int NPROD = 64 + NFFN;
constexpr int FSL = FF / NFFN;
#define NST 12
constexpr int STAGE = 16384;
constexpr int NTHREADS = 288;

constexpr int OFF_QPART = NST * STAGE;
constexpr int OFF_OPART = OFF_QPART + 8192;
constexpr int OFF_ML = OFF_OPART + 4096;
constexpr int OFF_QBF = OFF_ML + 128;
constexpr int OFF_RED = OFF_QBF + 256;
constexpr int OFF_BAR = OFF_RED + 256;
constexpr int SMEM_BYTES = OFF_BAR + (2 * NST + 2) * 8;

__device__ uint2 g_part[2 * 64 * NPROD * 8];
__device__ unsigned g_epoch[NCTA];

#define TL(i)

__device__ __forceinline__ void mbar_init(uint32_t bar, uint32_t cnt) {
    asm volatile("mbarrier.init.shared::cta.b64 [%0], %1;" ::"r"(bar), "r"(cnt) : "memory");
}
__device__ __forceinline__ void mbar_expect_tx(uint32_t bar, uint32_t bytes) {
    asm volatile("mbarrier.arrive.expect_tx.shared::cta.b64 _, [%0], %1;" ::"r"(bar), "r"(bytes) : "memory");
}
__device__ __forceinline__ void mbar_arrive(uint32_t bar) {
    asm volatile("mbarrier.arrive.shared::cta.b64 _, [%0];" ::"r"(bar) : "memory");
}
__device__ __forceinline__ bool mbar_try(uint32_t bar, uint32_t parity) {
    uint32_t ok;
    asm volatile(
        "{\n.reg .pred p;\nmbarrier.try_wait.parity.shared::cta.b64 p, [%1], %2;\nselp.u32 %0, 1, 0, p;\n}\n"
        : "=r"(ok) : "r"(bar), "r"(parity) : "memory");
    return ok;
}
__device__ __forceinline__ bool mbar_try_cluster(uint32_t bar, uint32_t parity) {
    uint32_t ok;
    asm volatile(
        "{\n.reg .pred p;\nmbarrier.try_wait.parity.acquire.cluster.shared::cta.b64 p, [%1], %2;\nselp.u32 %0, 1, 0, p;\n}\n"
        : "=r"(ok) : "r"(bar), "r"(parity) : "memory");
    return ok;
}
constexpr uint32_t SPIN_LIMIT = 1u << 22;
__device__ __forceinline__ void mbar_wait(uint32_t bar, uint32_t parity) {
    uint32_t n = 0;
    while (!mbar_try(bar, parity))
        if (++n > SPIN_LIMIT) __trap();
}
__device__ __forceinline__ void mbar_wait_cluster(uint32_t bar, uint32_t parity) {
    uint32_t n = 0;
    while (!mbar_try_cluster(bar, parity))
        if (++n > SPIN_LIMIT) __trap();
}
__device__ __forceinline__ void bulk_load(uint32_t dst, const void* src, uint32_t bytes, uint32_t bar) {
    asm volatile("cp.async.bulk.shared::cluster.global.mbarrier::complete_tx::bytes [%0], [%1], %2, [%3];"
                 ::"r"(dst), "l"(src), "r"(bytes), "r"(bar) : "memory");
}
__device__ __forceinline__ void bulk_load_hint(uint32_t dst, const void* src, uint32_t bytes, uint32_t bar, uint64_t pol) {
    asm volatile("cp.async.bulk.shared::cluster.global.mbarrier::complete_tx::bytes.L2::cache_hint [%0], [%1], %2, [%3], %4;"
                 ::"r"(dst), "l"(src), "r"(bytes), "r"(bar), "l"(pol) : "memory");
}
__device__ __forceinline__ uint4 ldg_nc(const void* p) {
    uint4 v;
    asm volatile("ld.global.nc.L1::no_allocate.v4.u32 {%0,%1,%2,%3}, [%4];"
                 : "=r"(v.x), "=r"(v.y), "=r"(v.z), "=r"(v.w) : "l"(p));
    return v;
}
__device__ __forceinline__ uint4 ldg_ca(const void* p) {
    uint4 v;
    asm volatile("ld.global.nc.v4.u32 {%0,%1,%2,%3}, [%4];"
                 : "=r"(v.x), "=r"(v.y), "=r"(v.z), "=r"(v.w) : "l"(p));
    return v;
}
__device__ __forceinline__ void ldsm4(uint32_t (&r)[4], uint32_t addr) {
    asm volatile("ldmatrix.sync.aligned.m8n8.x4.shared.b16 {%0,%1,%2,%3}, [%4];"
                 : "=r"(r[0]), "=r"(r[1]), "=r"(r[2]), "=r"(r[3]) : "r"(addr) : "memory");
}
__device__ __forceinline__ void ldsm4t(uint32_t (&r)[4], uint32_t addr) {
    asm volatile("ldmatrix.sync.aligned.m8n8.x4.trans.shared.b16 {%0,%1,%2,%3}, [%4];"
                 : "=r"(r[0]), "=r"(r[1]), "=r"(r[2]), "=r"(r[3]) : "r"(addr) : "memory");
}
__device__ __forceinline__ void mma16816(float (&d)[4], const uint32_t (&a)[4], uint32_t b0, uint32_t b1) {
    asm volatile(
        "mma.sync.aligned.m16n8k16.row.col.f32.bf16.bf16.f32 {%0,%1,%2,%3}, {%4,%5,%6,%7}, {%8,%9}, {%0,%1,%2,%3};"
        : "+f"(d[0]), "+f"(d[1]), "+f"(d[2]), "+f"(d[3])
        : "r"(a[0]), "r"(a[1]), "r"(a[2]), "r"(a[3]), "r"(b0), "r"(b1));
}
__device__ __forceinline__ uint32_t mapa(uint32_t addr, uint32_t rank) {
    uint32_t r;
    asm("mapa.shared::cluster.u32 %0, %1, %2;" : "=r"(r) : "r"(addr), "r"(rank));
    return r;
}
__device__ __forceinline__ void st_async_v4(uint32_t addr, float a, float b, float c, float d, uint32_t bar) {
    asm volatile("st.async.shared::cluster.mbarrier::complete_tx::bytes.v4.f32 [%0], {%1,%2,%3,%4}, [%5];"
                 ::"r"(addr), "f"(a), "f"(b), "f"(c), "f"(d), "r"(bar) : "memory");
}
__device__ __forceinline__ void st_async_v2(uint32_t addr, float a, float b, uint32_t bar) {
    asm volatile("st.async.shared::cluster.mbarrier::complete_tx::bytes.v2.f32 [%0], {%1,%2}, [%3];"
                 ::"r"(addr), "f"(a), "f"(b), "r"(bar) : "memory");
}
__device__ __forceinline__ float lds_f32(uint32_t addr) {
    float v;
    asm volatile("ld.shared.f32 %0, [%1];" : "=f"(v) : "r"(addr) : "memory");
    return v;
}
__device__ __forceinline__ float2 lds_f32x2(uint32_t addr) {
    float2 v;
    asm volatile("ld.shared.v2.f32 {%0,%1}, [%2];" : "=f"(v.x), "=f"(v.y) : "r"(addr) : "memory");
    return v;
}
__device__ __forceinline__ float4 lds_f32x4(uint32_t addr) {
    float4 v;
    asm volatile("ld.shared.v4.f32 {%0,%1,%2,%3}, [%4];" : "=f"(v.x), "=f"(v.y), "=f"(v.z), "=f"(v.w) : "r"(addr) : "memory");
    return v;
}
__device__ __forceinline__ uint32_t lds_u32(uint32_t addr) {
    uint32_t v;
    asm volatile("ld.shared.u32 %0, [%1];" : "=r"(v) : "r"(addr) : "memory");
    return v;
}
__device__ __forceinline__ uint32_t lds_u16(uint32_t addr) {
    uint16_t v;
    asm volatile("ld.shared.u16 %0, [%1];" : "=h"(v) : "r"(addr) : "memory");
    return v;
}
__device__ __forceinline__ void sts_u16(uint32_t addr, uint32_t v) {
    asm volatile("st.shared.u16 [%0], %1;" ::"r"(addr), "h"((uint16_t)v) : "memory");
}
__device__ __forceinline__ void sts_v4(uint32_t addr, uint32_t a, uint32_t b, uint32_t c, uint32_t d) {
    asm volatile("st.shared.v4.u32 [%0], {%1,%2,%3,%4};" ::"r"(addr), "r"(a), "r"(b), "r"(c), "r"(d) : "memory");
}
__device__ __forceinline__ void sts_f32x2(uint32_t addr, float a, float b) {
    asm volatile("st.shared.v2.f32 [%0], {%1,%2};" ::"r"(addr), "f"(a), "f"(b) : "memory");
}
__device__ __forceinline__ void bar_sync(int id, int n) { asm volatile("bar.sync %0, %1;" ::"r"(id), "r"(n) : "memory"); }
__device__ __forceinline__ void bar_arrive(int id, int n) { asm volatile("bar.arrive %0, %1;" ::"r"(id), "r"(n) : "memory"); }
__device__ __forceinline__ void cluster_arrive_release() { asm volatile("barrier.cluster.arrive.release.aligned;" ::: "memory"); }
__device__ __forceinline__ void cluster_arrive_relaxed() { asm volatile("barrier.cluster.arrive.relaxed.aligned;" ::: "memory"); }
__device__ __forceinline__ void cluster_wait() { asm volatile("barrier.cluster.wait.acquire.aligned;" ::: "memory"); }

__device__ __forceinline__ uint32_t pack_bf16(float lo, float hi) {
    uint32_t r;
    asm("cvt.rn.bf16x2.f32 %0, %1, %2;" : "=r"(r) : "f"(hi), "f"(lo));
    return r;
}
__device__ __forceinline__ float bf_lo(uint32_t v) { return __uint_as_float(v << 16); }
__device__ __forceinline__ float bf_hi(uint32_t v) { return __uint_as_float(v & 0xffff0000u); }
__device__ __forceinline__ float rbf(float x) { return bf_lo(pack_bf16(x, 0.f)); }
__device__ __forceinline__ float ex2(float x) {
    float r;
    asm("ex2.approx.ftz.f32 %0, %1;" : "=f"(r) : "f"(x));
    return r;
}
__device__ __forceinline__ float warp_max(float x) {
    int k = __float_as_int(x);
    k ^= (k >> 31) & 0x7fffffff;
    k = __reduce_max_sync(0xffffffffu, k);
    k ^= (k >> 31) & 0x7fffffff;
    return __int_as_float(k);
}
__device__ __forceinline__ float warp_sum(float x) {
#pragma unroll
    for (int o = 16; o > 0; o >>= 1) x += __shfl_xor_sync(0xffffffffu, x, o);
    return x;
}
__device__ __forceinline__ void unpack8(const uint4& v, float* f) {
    f[0] = bf_lo(v.x); f[1] = bf_hi(v.x); f[2] = bf_lo(v.y); f[3] = bf_hi(v.y);
    f[4] = bf_lo(v.z); f[5] = bf_hi(v.z); f[6] = bf_lo(v.w); f[7] = bf_hi(v.w);
}
__device__ __forceinline__ void ln_stats(const uint4& a, const uint4& b, float& mean_bf, float& sd_bf) {
    float f[16];
    unpack8(a, f); unpack8(b, f + 8);
    float s = 0.f;
#pragma unroll
    for (int i = 0; i < 16; i++) s += f[i];
    const float mean = warp_sum(s) * (1.f / DM);
    float q = 0.f;
#pragma unroll
    for (int i = 0; i < 16; i++) { const float d = f[i] - mean; q = fmaf(d, d, q); }
    const float var = warp_sum(q) * (1.f / DM);
    mean_bf = rbf(mean);
    sd_bf = rbf(__fsqrt_rn(rbf(rbf(var) + 1e-5f)));
}
__device__ __forceinline__ float ln_apply(float x, float mean_bf, float sd_bf) {
    return rbf(__fdiv_rn(rbf(x - mean_bf), sd_bf));
}
__device__ __forceinline__ float2 fold8(const float* c) {
    float v[8];
#pragma unroll
    for (int i = 0; i < 8; i++) v[i] = c[2 * i] + c[2 * (i ^ 1) + 1];
    const float w0 = v[0] + __shfl_xor_sync(0xffffffffu, v[2], 1);
    const float w1 = v[1] + __shfl_xor_sync(0xffffffffu, v[3], 1);
    const float w4 = v[4] + __shfl_xor_sync(0xffffffffu, v[6], 1);
    const float w5 = v[5] + __shfl_xor_sync(0xffffffffu, v[7], 1);
    return make_float2(w0 + __shfl_xor_sync(0xffffffffu, w4, 2), w1 + __shfl_xor_sync(0xffffffffu, w5, 2));
}
__device__ __forceinline__ void publish(int b, int prod, int warp, int lane, float2 y, uint32_t tag) {
    uint2* p = g_part + ((size_t)(b * 64 + warp * 8 + 2 * (lane & 3)) * NPROD + prod) * 8 + (lane >> 2);
    const unsigned long long t = (unsigned long long)tag << 32;
    asm volatile("st.relaxed.gpu.global.b64 [%0], %1;" ::"l"(p), "l"(t | __float_as_uint(y.x)) : "memory");
    asm volatile("st.relaxed.gpu.global.b64 [%0], %1;" ::"l"(p + NPROD * 8), "l"(t | __float_as_uint(y.y)) : "memory");
}
__device__ __forceinline__ float2 gather(const uint2* p, uint32_t tag) {
    unsigned long long a, b;
    uint32_t n = 0;
    while (true) {
        asm volatile("ld.relaxed.gpu.global.v2.b64 {%0,%1}, [%2];" : "=l"(a), "=l"(b) : "l"(p) : "memory");
        if ((uint32_t)(a >> 32) == tag && (uint32_t)(b >> 32) == tag) break;
        if (++n > SPIN_LIMIT) __trap();
        __nanosleep(20);
    }
    return make_float2(__uint_as_float((uint32_t)a), __uint_as_float((uint32_t)b));
}

__global__ void __cluster_dims__(2, 1, 1) __launch_bounds__(NTHREADS, 1)
fused_decode_kernel(const __nv_bfloat16* __restrict__ x, const __nv_bfloat16* __restrict__ kc,
                    const __nv_bfloat16* __restrict__ vc, const __nv_bfloat16* __restrict__ wq,
                    const __nv_bfloat16* __restrict__ wo, const __nv_bfloat16* __restrict__ w1,
                    const __nv_bfloat16* __restrict__ b1, const __nv_bfloat16* __restrict__ w2,
                    const __nv_bfloat16* __restrict__ b2, __nv_bfloat16* __restrict__ out) {
    extern __shared__ __align__(1024) unsigned char smem[];
    const uint32_t sb = (uint32_t)__cvta_generic_to_shared(smem);
    const uint32_t full0 = sb + OFF_BAR, empty0 = full0 + NST * 8, qbar = empty0 + NST * 8, obar = qbar + 8;
    const int tid = threadIdx.x, warp = tid >> 5, lane = tid & 31;
    const int cta = blockIdx.x;
    const int g = lane >> 2, c = lane & 3;

    if (cta < NATT) {
        const int rank = cta & 1, b = (cta >> 1) & 1, h = cta >> 2;
        if (warp == 8) {
            const size_t kvoff = ((size_t)(b * NH + h) * SK + (SK - WIN) + rank * (WIN / 2)) * DH;
            const char* kp = (const char*)(kc + kvoff);
            const char* vp = (const char*)(vc + kvoff);
            const char* wp = (const char*)(wo + (size_t)(h * DH + rank * 64) * DM);
            uint64_t pol;
            asm volatile("createpolicy.fractional.L2::evict_first.b64 %0, 1.0;" : "=l"(pol));
            if (lane == 0) {
                TL(0);
#pragma unroll
                for (int s = 0; s < NST; s++) { mbar_init(full0 + 8 * s, 1); mbar_init(empty0 + 8 * s, 4); }
                mbar_init(qbar, 1);
                mbar_init(obar, 1);
                asm volatile("fence.mbarrier_init.release.cluster;" ::: "memory");
                mbar_expect_tx(qbar, 16 * 512);
                mbar_expect_tx(obar, 16 * (256 + 8));
            }
            __syncwarp();
            cluster_arrive_release();
            if (lane == 0) {
#pragma unroll
                for (int s = 0; s < NST; s++) {
                    mbar_expect_tx(full0 + 8 * s, STAGE);
                    bulk_load_hint(sb + s * STAGE, ((s & 1) ? vp : kp) + (s >> 1) * STAGE, STAGE, full0 + 8 * s, pol);
                }
                TL(1);
            }
            __syncwarp();
            const uint32_t tag = g_epoch[cta] + 1;
            const int ob = cta >> 6, oc = cta & 63;
            const float xo = __bfloat162float(x[ob * DM + oc * 8 + (lane & 7)]);
            const float bo = __bfloat162float(b2[oc * 8 + (lane & 7)]);
            cluster_wait();
            if (lane == 0) {
                int s = 0, ph = 0;
#pragma unroll 1
                for (int i = NST; i < 68; i++) {
                    mbar_wait(empty0 + 8 * s, ph);
                    mbar_expect_tx(full0 + 8 * s, STAGE);
                    if (i < 64) bulk_load_hint(sb + s * STAGE, ((i & 1) ? vp : kp) + (i >> 1) * STAGE, STAGE, full0 + 8 * s, pol);
                    else bulk_load(sb + s * STAGE, wp + (i - 64) * STAGE, STAGE, full0 + 8 * s);
                    if (++s == NST) { s = 0; ph ^= 1; }
                }
                TL(2);
            }
            __syncwarp();
            float2 f = make_float2(0.f, 0.f);
            if (lane < 4 * NFFN) f = gather(g_part + ((size_t)cta * NPROD + 64) * 8 + lane * 2, tag);
            __syncwarp();
            f.x += __shfl_xor_sync(0xffffffffu, f.x, 4); f.y += __shfl_xor_sync(0xffffffffu, f.y, 4);
            f.x += __shfl_xor_sync(0xffffffffu, f.x, 8); f.y += __shfl_xor_sync(0xffffffffu, f.y, 8);
            const float fx = __shfl_sync(0xffffffffu, f.x, (lane & 7) >> 1), fy = __shfl_sync(0xffffffffu, f.y, (lane & 7) >> 1);
            const float ffn = rbf(rbf((lane & 1) ? fy : fx) + bo);
            if (lane == 0) g_epoch[cta] = tag;
            bar_sync(2, NTHREADS);
            float a = lds_f32(sb + OFF_RED + lane * 4) + lds_f32(sb + OFF_RED + 128 + lane * 4);
            a += __shfl_xor_sync(0xffffffffu, a, 8);
            a += __shfl_xor_sync(0xffffffffu, a, 16);
            if (lane < 8) out[ob * DM + oc * 8 + lane] = __float2bfloat16_rn(rbf(xo + rbf(a)) + ffn);
            if (lane == 0) TL(3);
        } else {
            uint32_t qf[8][2];
            uint32_t tag;
            {
                const int hw = tid >> 4, c16 = tid & 15;
                const uint4 xs0 = ldg_ca(x + b * DM + lane * 16), xs1 = ldg_ca(x + b * DM + lane * 16 + 8);
                const uint4 xr0 = ldg_ca(x + b * DM + rank * 256 + hw * 16), xr1 = ldg_ca(x + b * DM + rank * 256 + hw * 16 + 8);
                const __nv_bfloat16* wqp = wq + (size_t)(rank * 256 + hw * 16) * (NH * DH) + h * DH + c16 * 8;
                uint4 wv[16];
#pragma unroll
                for (int i = 0; i < 16; i++) wv[i] = ldg_nc(wqp + (size_t)i * (NH * DH));
                tag = g_epoch[cta] + 1;
                cluster_arrive_relaxed();
                float mean_bf, sd_bf, xn[16];
                ln_stats(xs0, xs1, mean_bf, sd_bf);
                unpack8(xr0, xn); unpack8(xr1, xn + 8);
#pragma unroll
                for (int i = 0; i < 16; i++) xn[i] = ln_apply(xn[i], mean_bf, sd_bf);
                if (tid == 0) TL(4);
                float acc[8];
#pragma unroll
                for (int k = 0; k < 8; k++) acc[k] = 0.f;
#pragma unroll
                for (int i = 0; i < 16; i++) {
                    float w[8];
                    unpack8(wv[i], w);
#pragma unroll
                    for (int k = 0; k < 8; k++) acc[k] = fmaf(xn[i], w[k], acc[k]);
                }
#pragma unroll
                for (int k = 0; k < 8; k++) acc[k] += __shfl_xor_sync(0xffffffffu, acc[k], 16);
                cluster_wait();
                const uint32_t dst = mapa(sb + OFF_QPART + (rank * 8 + warp) * 512 + c16 * 32, lane >> 4);
                const uint32_t dbar = mapa(qbar, lane >> 4);
                st_async_v4(dst, acc[0], acc[1], acc[2], acc[3], dbar);
                st_async_v4(dst + 16, acc[4], acc[5], acc[6], acc[7], dbar);
                if (tid == 0) TL(5);
                if (tid < 128) {
                    mbar_wait_cluster(qbar, 0);
                    float s = 0.f;
#pragma unroll
                    for (int i = 0; i < 16; i++) s += lds_f32(sb + OFF_QPART + i * 512 + tid * 4);
                    sts_u16(sb + OFF_QBF + tid * 2, pack_bf16(s, 0.f));
                }
                bar_sync(1, 256);
#pragma unroll
                for (int j = 0; j < 8; j++) {
                    qf[j][0] = lds_u32(sb + OFF_QBF + ((j ^ g) * 16) + c * 4);
                    qf[j][1] = lds_u32(sb + OFF_QBF + 128 + ((j ^ g) * 16) + c * 4);
                }
                if (tid == 0) TL(6);
            }
            const int r = lane & 7, mi = lane >> 3;
            const uint32_t koff = ((warp & 3) * 16 + r + 8 * (mi & 1)) * 256 + (mi >> 1) * 128 + r * 16;
            const uint32_t voff = ((warp & 3) * 16 + r + 8 * (mi >> 1)) * 256 + (mi & 1) * 128 + r * 16;
            const bool diag = (c == (g >> 1));
            const bool e = g & 1;
            const uint32_t sel0 = e ? 0x1044u : 0x4410u, sel1 = e ? 0x3244u : 0x4432u;
            float o[8][4];
#pragma unroll
            for (int j = 0; j < 8; j++) { o[j][0] = o[j][1] = o[j][2] = o[j][3] = 0.f; }
            float m = -INFINITY, l = 0.f;
            constexpr float LOG2E = 1.4426950408889634f;
            int s = 2 * (warp >> 2), ph = 0;
#pragma unroll 1
            for (int it = 0; it < 16; it++) {
                const uint32_t kb = sb + s * STAGE + koff;
                mbar_wait(full0 + 8 * s, ph);
                float sa[4] = {0.f, 0.f, 0.f, 0.f}, sc[4] = {0.f, 0.f, 0.f, 0.f};
                {
                    uint32_t a[8][4];
#pragma unroll
                    for (int j = 0; j < 8; j++) ldsm4(a[j], kb ^ (j << 4));
#pragma unroll
                    for (int j = 0; j < 8; j += 2) {
                        mma16816(sa, a[j], qf[j][0], qf[j][1]);
                        mma16816(sc, a[j + 1], qf[j + 1][0], qf[j + 1][1]);
                    }
                }
                __syncwarp();
                if (lane == 0) mbar_arrive(empty0 + 8 * s);
                int s2 = s + 1, ph2 = ph;
                if (NST & 1) { if (s2 == NST) { s2 = 0; ph2 ^= 1; } }
                uint32_t pk = pack_bf16(e ? sa[1] + sc[1] : sa[0] + sc[0], e ? sa[3] + sc[3] : sa[2] + sc[2]);
                pk = pack_bf16(bf_lo(pk) * 0.08838834764831845f, bf_hi(pk) * 0.08838834764831845f);
                const float s0 = diag ? bf_lo(pk) : -INFINITY, s1 = diag ? bf_hi(pk) : -INFINITY;
                const float mx = warp_max(fmaxf(s0, s1));
                if (mx > m) {
                    const float sc_ = ex2((m - mx) * LOG2E);
                    m = mx;
                    l *= sc_;
#pragma unroll
                    for (int j = 0; j < 8; j++) { o[j][0] *= sc_; o[j][1] *= sc_; o[j][2] *= sc_; o[j][3] *= sc_; }
                }
                const float p0 = ex2((s0 - m) * LOG2E), p1 = ex2((s1 - m) * LOG2E);
                l += p0 + p1;
                pk = pack_bf16(p0, p1);
                const uint32_t pb0 = __byte_perm(pk, 0, sel0), pb1 = __byte_perm(pk, 0, sel1);
                const uint32_t vb = sb + s2 * STAGE + voff;
                mbar_wait(full0 + 8 * s2, ph2);
                {
                    uint32_t a[8][4];
#pragma unroll
                    for (int j = 0; j < 8; j++) ldsm4t(a[j], vb ^ (j << 4));
#pragma unroll
                    for (int j = 0; j < 8; j++) mma16816(o[j], a[j], pb0, pb1);
                }
                __syncwarp();
                if (lane == 0) mbar_arrive(empty0 + 8 * s2);
                s += 4;
                if (s >= NST) { s -= NST; ph ^= 1; }
            }
            if (tid == 224) TL(7);
            {
                float lo[16], hi[16];
#pragma unroll
                for (int j = 0; j < 8; j++) { lo[2 * j] = o[j][0]; lo[2 * j + 1] = o[j][1]; hi[2 * j] = o[j][2]; hi[2 * j + 1] = o[j][3]; }
                const float2 u0 = fold8(lo), u1 = fold8(hi);
                l = warp_sum(l);
                const uint32_t slot = sb + OFF_OPART + (rank * 8 + warp) * 256 + lane * 8;
                st_async_v2(mapa(slot, 0), u0.x, u0.y, mapa(obar, 0));
                st_async_v2(mapa(slot, 1), u1.x, u1.y, mapa(obar, 1));
                if (lane < 2) st_async_v2(mapa(sb + OFF_ML + (rank * 8 + warp) * 8, lane), m, l, mapa(obar, lane));
            }
            const int kk = c ^ (g >> 1);
            uint32_t ob0, ob1;
            {
                mbar_wait_cluster(obar, 0);
                if (tid == 224) TL(8);
                float mw[16], lw[16];
#pragma unroll
                for (int i = 0; i < 8; i++) {
                    const float4 t = lds_f32x4(sb + OFF_ML + i * 16);
                    mw[2 * i] = t.x; lw[2 * i] = t.y; mw[2 * i + 1] = t.z; lw[2 * i + 1] = t.w;
                }
                float M = mw[0];
#pragma unroll
                for (int i = 1; i < 16; i++) M = fmaxf(M, mw[i]);
                const uint32_t src = sb + OFF_OPART + (4 * (2 * c + (g & 1)) + kk) * 8;
                float L = 0.f, o0 = 0.f, o1 = 0.f;
#pragma unroll
                for (int i = 0; i < 16; i++) {
                    const float f = ex2((mw[i] - M) * LOG2E);
                    const float2 t = lds_f32x2(src + i * 256);
                    L = fmaf(f, lw[i], L);
                    o0 = fmaf(f, t.x, o0);
                    o1 = fmaf(f, t.y, o1);
                }
                const float inv = __fdividef(1.f, L);
                const uint32_t pk = pack_bf16(o0 * inv, o1 * inv);
                ob0 = __byte_perm(pk, 0, sel0);
                ob1 = __byte_perm(pk, 0, sel1);
            }
            float y[4][4];
#pragma unroll
            for (int j = 0; j < 4; j++) { y[j][0] = y[j][1] = y[j][2] = y[j][3] = 0.f; }
#pragma unroll
            for (int t = 0; t < 4; t++) {
                const int st = (64 + t) % NST, pt = ((64 + t) / NST) & 1;
                mbar_wait(full0 + 8 * st, pt);
                const uint32_t wb = sb + st * STAGE + (r + 8 * (mi >> 1)) * 1024 + warp * 128 + (((mi & 1) * 4) ^ r ^ (2 * t)) * 16;
                uint32_t a[4][4];
#pragma unroll
                for (int j = 0; j < 4; j++) ldsm4t(a[j], wb ^ (j << 4));
                const uint32_t f0 = (kk == t) ? ob0 : 0u, f1 = (kk == t) ? ob1 : 0u;
#pragma unroll
                for (int j = 0; j < 4; j++) mma16816(y[j], a[j], f0, f1);
            }
            if (tid == 224) TL(9);
            float yy[16];
#pragma unroll
            for (int j = 0; j < 4; j++) { yy[2 * j] = y[j][0]; yy[2 * j + 1] = y[j][1]; yy[8 + 2 * j] = y[j][2]; yy[8 + 2 * j + 1] = y[j][3]; }
            publish(b, h * 2 + rank, warp, lane, fold8(yy), tag);
            if (tid == 224) TL(10);
            float2 t = gather(g_part + (size_t)cta * NPROD * 8 + tid * 2, tag);
            __syncwarp();
            if (tid == 224) TL(11);
#pragma unroll
            for (int ofs = 4; ofs < 32; ofs <<= 1) {
                t.x += __shfl_xor_sync(0xffffffffu, t.x, ofs);
                t.y += __shfl_xor_sync(0xffffffffu, t.y, ofs);
            }
            if (lane < 4) sts_f32x2(sb + OFF_RED + warp * 32 + lane * 8, t.x, t.y);
            bar_arrive(2, NTHREADS);
        }
    } else {
        const int fj = cta - NATT;
        constexpr int T1 = 32, T2 = 22;
        if (warp == 8) {
            if (lane == 0) {
                TL(0);
#pragma unroll
                for (int s = 0; s < NST; s++) { mbar_init(full0 + 8 * s, 1); mbar_init(empty0 + 8 * s, 8); }
                asm volatile("fence.mbarrier_init.release.cluster;" ::: "memory");
            }
            __syncwarp();
            bar_arrive(3, NTHREADS);
            const char* p1 = (const char*)(w1 + (size_t)(lane & 15) * FF + fj * FSL);
            const char* p2 = (const char*)(w2 + (size_t)fj * FSL * DM);
            int s = 0, ph = 1;
#pragma unroll 1
            for (int i = 0; i < T1 + T2; i++) {
                mbar_wait(empty0 + 8 * s, ph);
                if (i < T1) {
                    if (lane == 0) mbar_expect_tx(full0 + 8 * s, 16 * FSL * 2);
                    __syncwarp();
                    if (lane < 16) bulk_load(sb + s * STAGE + lane * (FSL * 2), p1 + (size_t)i * 16 * FF * 2, FSL * 2, full0 + 8 * s);
                } else if (lane == 0) {
                    const uint32_t bytes = (i == T1 + T2 - 1) ? STAGE / 2 : STAGE;
                    mbar_expect_tx(full0 + 8 * s, bytes);
                    bulk_load(sb + s * STAGE, p2 + (size_t)(i - T1) * STAGE, bytes, full0 + 8 * s);
                }
                __syncwarp();
                if (++s == NST) { s = 0; ph ^= 1; }
            }
        } else {
            const uint32_t xn_s = sb + OFF_QPART;
            const uint32_t g_s = xn_s + 2048;
            const uint32_t tag = g_epoch[cta] + 1;
            if (warp < 2) {
                const uint4 xs0 = ldg_ca(x + warp * DM + lane * 16), xs1 = ldg_ca(x + warp * DM + lane * 16 + 8);
                float mean_bf, sd_bf, xn[16];
                ln_stats(xs0, xs1, mean_bf, sd_bf);
                unpack8(xs0, xn); unpack8(xs1, xn + 8);
                uint32_t pk[8];
#pragma unroll
                for (int i = 0; i < 8; i++) pk[i] = pack_bf16(ln_apply(xn[2 * i], mean_bf, sd_bf), ln_apply(xn[2 * i + 1], mean_bf, sd_bf));
                sts_v4(xn_s + warp * 1024 + lane * 32, pk[0], pk[1], pk[2], pk[3]);
                sts_v4(xn_s + warp * 1024 + lane * 32 + 16, pk[4], pk[5], pk[6], pk[7]);
            }
            bar_sync(3, NTHREADS);
            const int r = lane & 7, mi = lane >> 3;
            int s = 0, ph = 0;
            float hacc[3][4];
#pragma unroll
            for (int j = 0; j < 3; j++) { hacc[j][0] = hacc[j][1] = hacc[j][2] = hacc[j][3] = 0.f; }
            uint32_t aoff[3];
#pragma unroll
            for (int j = 0; j < 3; j++) aoff[j] = (r + 8 * (mi >> 1)) * (FSL * 2) + min(2 * (warp + 8 * j) + (mi & 1), FSL / 8 - 1) * 16;
#pragma unroll 1
            for (int i = 0; i < T1; i++) {
                uint32_t f0 = 0, f1 = 0;
                if (g < 2) { f0 = lds_u32(xn_s + g * 1024 + i * 32 + c * 4); f1 = lds_u32(xn_s + g * 1024 + i * 32 + 16 + c * 4); }
                mbar_wait(full0 + 8 * s, ph);
#pragma unroll
                for (int j = 0; j < 3; j++) {
                    uint32_t a[4];
                    ldsm4t(a, sb + s * STAGE + aoff[j]);
                    mma16816(hacc[j], a, f0, f1);
                }
                __syncwarp();
                if (lane == 0) mbar_arrive(empty0 + 8 * s);
                if (++s == NST) { s = 0; ph ^= 1; }
            }
            if (c == 0) {
#pragma unroll
                for (int j = 0; j < 3; j++)
#pragma unroll
                    for (int hf = 0; hf < 2; hf++) {
                        const int f = (warp + 8 * j) * 16 + hf * 8 + g;
                        if (f < FSL + 8) {
                            const float bias = f < FSL ? __bfloat162float(b1[fj * FSL + f]) : 0.f;
#pragma unroll
                            for (int bb = 0; bb < 2; bb++) {
                                const float hv = rbf(rbf(hacc[j][2 * hf + bb]) + bias);
                                const float inner = 0.7978845608028654f * (hv + 0.044715f * hv * hv * hv);
                                const float gv = f < FSL ? 0.5f * hv * (1.f + tanhf(inner)) : 0.f;
                                sts_u16(g_s + bb * 704 + f * 2, pack_bf16(gv, 0.f));
                            }
                        }
                    }
            }
            bar_sync(1, 256);
            float y[2][4][4];
#pragma unroll
            for (int bb = 0; bb < 2; bb++)
#pragma unroll
                for (int j = 0; j < 4; j++) { y[bb][j][0] = y[bb][j][1] = y[bb][j][2] = y[bb][j][3] = 0.f; }
            const bool diag = (c == (g >> 1));
            const int sh = (g & 1) * 16;
#pragma unroll 1
            for (int i = 0; i < T2; i++) {
                uint32_t f[2][2] = {{0u, 0u}, {0u, 0u}};
                if (diag) {
#pragma unroll
                    for (int bb = 0; bb < 2; bb++) {
                        f[bb][0] = lds_u16(g_s + bb * 704 + (i * 16 + g) * 2) << sh;
                        f[bb][1] = lds_u16(g_s + bb * 704 + (i * 16 + 8 + g) * 2) << sh;
                    }
                }
                const int up = (i == T2 - 1) ? 0 : (mi >> 1);
                const uint32_t wb = sb + s * STAGE + (r + 8 * up) * 1024 + warp * 128 + (((mi & 1) * 4) ^ r) * 16;
                mbar_wait(full0 + 8 * s, ph);
#pragma unroll
                for (int j = 0; j < 4; j++) {
                    uint32_t a[4];
                    ldsm4t(a, wb ^ (j << 4));
                    mma16816(y[0][j], a, f[0][0], f[0][1]);
                    mma16816(y[1][j], a, f[1][0], f[1][1]);
                }
                __syncwarp();
                if (lane == 0) mbar_arrive(empty0 + 8 * s);
                if (++s == NST) { s = 0; ph ^= 1; }
            }
#pragma unroll
            for (int bb = 0; bb < 2; bb++) {
                float yy[16];
#pragma unroll
                for (int j = 0; j < 4; j++) { yy[2 * j] = y[bb][j][0]; yy[2 * j + 1] = y[bb][j][1]; yy[8 + 2 * j] = y[bb][j][2]; yy[8 + 2 * j + 1] = y[bb][j][3]; }
                publish(bb, 64 + fj, warp, lane, fold8(yy), tag);
            }
            if (tid == 0) { g_epoch[cta] = tag; TL(3); }
        }
    }
}

}

extern "C" void kernel_launch(void* const* d_in, const int* in_sizes, int n_in, void* d_out, int out_size) {
    (void)in_sizes; (void)n_in; (void)out_size;
    static bool attr_set = false;
    if (!attr_set) {
        cudaFuncSetAttribute(fused_decode_kernel, cudaFuncAttributeMaxDynamicSharedMemorySize, SMEM_BYTES);
        attr_set = true;
    }
    typedef const __nv_bfloat16* P;
    fused_decode_kernel<<<NCTA, NTHREADS, SMEM_BYTES>>>((P)d_in[0], (P)d_in[1], (P)d_in[2], (P)d_in[3], (P)d_in[4],
                                                        (P)d_in[6], (P)d_in[7], (P)d_in[8], (P)d_in[9],
                                                        (__nv_bfloat16*)d_out);
}
```

```cpp
#include <cuda.h>
#include <cuda_runtime.h>
#include <cuda_bf16.h>
#include <stdint.h>

namespace {

constexpr int DM = 512, NH = 32, SK = 16384, WIN = 4096, DH = 128, FF = 1376;
constexpr int NATT = 128, NFFN = 4, NCTA = NATT + NFFN;
constexpr int NPROD = 64 + NFFN;
constexpr int FSL = 352;
#define NST 12
#define PRE 2
#define RED_MODE 1
#define ACC_STRIDE 1
constexpr int STAGE = 16384;
constexpr int NTHREADS = 288;

constexpr int OFF_QPART = NST * STAGE;
constexpr int OFF_S = OFF_QPART, OFF_P = OFF_QPART + 4096;
constexpr int OFF_OPART = OFF_QPART + 8192;
constexpr int OFF_ML = OFF_OPART + 512;
constexpr int OFF_QBF = OFF_ML + 128;
constexpr int OFF_BAR = OFF_QBF + 256;
constexpr int SMEM_BYTES = OFF_BAR + (2 * NST + 3) * 8;

__device__ float4 g_acc[2 * 256 * ACC_STRIDE];

struct Params {
    const __nv_bfloat16 *kc, *x, *wo;
    float4* acc;
    __nv_bfloat16* out;
    const __nv_bfloat16 *w2, *b1, *b2;
    unsigned long long* tl;
};
struct Maps {
    alignas(64) CUtensorMap wq, v, w1;
};

#define TL(i)
#define TT(i)

__device__ __forceinline__ void mbar_init(uint32_t bar, uint32_t cnt) {
    asm volatile("mbarrier.init.shared::cta.b64 [%0], %1;" ::"r"(bar), "r"(cnt) : "memory");
}
__device__ __forceinline__ void mbar_expect_tx(uint32_t bar, uint32_t bytes) {
    asm volatile("mbarrier.arrive.expect_tx.shared::cta.b64 _, [%0], %1;" ::"r"(bar), "r"(bytes) : "memory");
}
__device__ __forceinline__ void mbar_arrive2(uint32_t bar) {
    asm volatile("mbarrier.arrive.shared::cta.b64 _, [%0], 2;" ::"r"(bar) : "memory");
}
__device__ __forceinline__ void mbar_arrive(uint32_t bar) {
    asm volatile("mbarrier.arrive.shared::cta.b64 _, [%0];" ::"r"(bar) : "memory");
}
__device__ __forceinline__ bool mbar_try(uint32_t bar, uint32_t parity) {
    uint32_t ok;
    asm volatile(
        "{\n.reg .pred p;\nmbarrier.try_wait.parity.shared::cta.b64 p, [%1], %2;\nselp.u32 %0, 1, 0, p;\n}\n"
        : "=r"(ok) : "r"(bar), "r"(parity) : "memory");
    return ok;
}
__device__ __forceinline__ bool mbar_try_cluster(uint32_t bar, uint32_t parity) {
    uint32_t ok;
    asm volatile(
        "{\n.reg .pred p;\nmbarrier.try_wait.parity.acquire.cluster.shared::cta.b64 p, [%1], %2;\nselp.u32 %0, 1, 0, p;\n}\n"
        : "=r"(ok) : "r"(bar), "r"(parity) : "memory");
    return ok;
}
constexpr uint32_t SPIN_LIMIT = 1u << 22;
__device__ __forceinline__ void mbar_wait(uint32_t bar, uint32_t parity) {
    uint32_t n = 0;
    while (!mbar_try(bar, parity))
        if (++n > SPIN_LIMIT) __trap();
}
__device__ __forceinline__ void mbar_wait_cluster(uint32_t bar, uint32_t parity) {
    uint32_t n = 0;
    while (!mbar_try_cluster(bar, parity))
        if (++n > SPIN_LIMIT) __trap();
}
__device__ __forceinline__ void bulk_load(uint32_t dst, const void* src, uint32_t bytes, uint32_t bar) {
    asm volatile("cp.async.bulk.shared::cluster.global.mbarrier::complete_tx::bytes [%0], [%1], %2, [%3];"
                 ::"r"(dst), "l"(src), "r"(bytes), "r"(bar) : "memory");
}
__device__ __forceinline__ void bulk_load_hint(uint32_t dst, const void* src, uint32_t bytes, uint32_t bar, uint64_t pol) {
    asm volatile("cp.async.bulk.shared::cluster.global.mbarrier::complete_tx::bytes.L2::cache_hint [%0], [%1], %2, [%3], %4;"
                 ::"r"(dst), "l"(src), "r"(bytes), "r"(bar), "l"(pol) : "memory");
}
__device__ __forceinline__ uint4 ldg_nc(const void* p) {
    uint4 v;
    asm volatile("ld.global.nc.L1::no_allocate.v4.u32 {%0,%1,%2,%3}, [%4];"
                 : "=r"(v.x), "=r"(v.y), "=r"(v.z), "=r"(v.w) : "l"(p));
    return v;
}
__device__ __forceinline__ uint4 ldg_na(const void* p) {
    uint4 v;
    asm volatile("ld.global.L1::no_allocate.v4.u32 {%0,%1,%2,%3}, [%4];"
                 : "=r"(v.x), "=r"(v.y), "=r"(v.z), "=r"(v.w) : "l"(p) : "memory");
    return v;
}
__device__ __forceinline__ uint32_t ldg_u32(const void* p) {
    uint32_t v;
    asm volatile("ld.global.u32 %0, [%1];" : "=r"(v) : "l"(p) : "memory");
    return v;
}
__device__ __forceinline__ uint32_t ldg_u16(const void* p) {
    uint16_t v;
    asm volatile("ld.global.u16 %0, [%1];" : "=h"(v) : "l"(p) : "memory");
    return v;
}
__device__ __forceinline__ uint4 ldg_ca(const void* p) {
    uint4 v;
    asm volatile("ld.global.nc.v4.u32 {%0,%1,%2,%3}, [%4];"
                 : "=r"(v.x), "=r"(v.y), "=r"(v.z), "=r"(v.w) : "l"(p));
    return v;
}
__device__ __forceinline__ void ldsm4(uint32_t (&r)[4], uint32_t addr) {
    asm volatile("ldmatrix.sync.aligned.m8n8.x4.shared.b16 {%0,%1,%2,%3}, [%4];"
                 : "=r"(r[0]), "=r"(r[1]), "=r"(r[2]), "=r"(r[3]) : "r"(addr) : "memory");
}
__device__ __forceinline__ void ldsm4t(uint32_t (&r)[4], uint32_t addr) {
    asm volatile("ldmatrix.sync.aligned.m8n8.x4.trans.shared.b16 {%0,%1,%2,%3}, [%4];"
                 : "=r"(r[0]), "=r"(r[1]), "=r"(r[2]), "=r"(r[3]) : "r"(addr) : "memory");
}
__device__ __forceinline__ void mma16816(float (&d)[4], const uint32_t (&a)[4], uint32_t b0, uint32_t b1) {
    asm volatile(
        "mma.sync.aligned.m16n8k16.row.col.f32.bf16.bf16.f32 {%0,%1,%2,%3}, {%4,%5,%6,%7}, {%8,%9}, {%0,%1,%2,%3};"
        : "+f"(d[0]), "+f"(d[1]), "+f"(d[2]), "+f"(d[3])
        : "r"(a[0]), "r"(a[1]), "r"(a[2]), "r"(a[3]), "r"(b0), "r"(b1));
}
__device__ __forceinline__ uint32_t mapa(uint32_t addr, uint32_t rank) {
    uint32_t r;
    asm("mapa.shared::cluster.u32 %0, %1, %2;" : "=r"(r) : "r"(addr), "r"(rank));
    return r;
}
__device__ __forceinline__ void st_async_v4(uint32_t addr, float a, float b, float c, float d, uint32_t bar) {
    asm volatile("st.async.shared::cluster.mbarrier::complete_tx::bytes.v4.f32 [%0], {%1,%2,%3,%4}, [%5];"
                 ::"r"(addr), "f"(a), "f"(b), "f"(c), "f"(d), "r"(bar) : "memory");
}
__device__ __forceinline__ void st_async_v2(uint32_t addr, float a, float b, uint32_t bar) {
    asm volatile("st.async.shared::cluster.mbarrier::complete_tx::bytes.v2.f32 [%0], {%1,%2}, [%3];"
                 ::"r"(addr), "f"(a), "f"(b), "r"(bar) : "memory");
}
__device__ __forceinline__ float lds_f32(uint32_t addr) {
    float v;
    asm volatile("ld.shared.f32 %0, [%1];" : "=f"(v) : "r"(addr) : "memory");
    return v;
}
__device__ __forceinline__ float2 lds_f32x2(uint32_t addr) {
    float2 v;
    asm volatile("ld.shared.v2.f32 {%0,%1}, [%2];" : "=f"(v.x), "=f"(v.y) : "r"(addr) : "memory");
    return v;
}
__device__ __forceinline__ float4 lds_f32x4(uint32_t addr) {
    float4 v;
    asm volatile("ld.shared.v4.f32 {%0,%1,%2,%3}, [%4];" : "=f"(v.x), "=f"(v.y), "=f"(v.z), "=f"(v.w) : "r"(addr) : "memory");
    return v;
}
__device__ __forceinline__ uint32_t lds_u32(uint32_t addr) {
    uint32_t v;
    asm volatile("ld.shared.u32 %0, [%1];" : "=r"(v) : "r"(addr) : "memory");
    return v;
}
__device__ __forceinline__ uint32_t lds_u16(uint32_t addr) {
    uint16_t v;
    asm volatile("ld.shared.u16 %0, [%1];" : "=h"(v) : "r"(addr) : "memory");
    return v;
}
__device__ __forceinline__ void sts_u16(uint32_t addr, uint32_t v) {
    asm volatile("st.shared.u16 [%0], %1;" ::"r"(addr), "h"((uint16_t)v) : "memory");
}
__device__ __forceinline__ void sts_v4(uint32_t addr, uint32_t a, uint32_t b, uint32_t c, uint32_t d) {
    asm volatile("st.shared.v4.u32 [%0], {%1,%2,%3,%4};" ::"r"(addr), "r"(a), "r"(b), "r"(c), "r"(d) : "memory");
}
__device__ __forceinline__ void sts_f32x2(uint32_t addr, float a, float b) {
    asm volatile("st.shared.v2.f32 [%0], {%1,%2};" ::"r"(addr), "f"(a), "f"(b) : "memory");
}
__device__ __forceinline__ void bar_sync(int id, int n) { asm volatile("bar.sync %0, %1;" ::"r"(id), "r"(n) : "memory"); }
__device__ __forceinline__ void bar_arrive(int id, int n) { asm volatile("bar.arrive %0, %1;" ::"r"(id), "r"(n) : "memory"); }
__device__ __forceinline__ void cluster_arrive_release() { asm volatile("barrier.cluster.arrive.release.aligned;" ::: "memory"); }
__device__ __forceinline__ void cluster_arrive_relaxed() { asm volatile("barrier.cluster.arrive.relaxed.aligned;" ::: "memory"); }
__device__ __forceinline__ void cluster_wait() { asm volatile("barrier.cluster.wait.acquire.aligned;" ::: "memory"); }

__device__ __forceinline__ uint32_t pack_bf16(float lo, float hi) {
    uint32_t r;
    asm("cvt.rn.bf16x2.f32 %0, %1, %2;" : "=r"(r) : "f"(hi), "f"(lo));
    return r;
}
__device__ __forceinline__ float bf_lo(uint32_t v) { return __uint_as_float(v << 16); }
__device__ __forceinline__ float bf_hi(uint32_t v) { return __uint_as_float(v & 0xffff0000u); }
__device__ __forceinline__ float rbf(float x) { return bf_lo(pack_bf16(x, 0.f)); }
__device__ __forceinline__ float ex2(float x) {
    float r;
    asm("ex2.approx.ftz.f32 %0, %1;" : "=f"(r) : "f"(x));
    return r;
}
__device__ __forceinline__ float warp_max(float x) {
    int k = __float_as_int(x);
    k ^= (k >> 31) & 0x7fffffff;
    k = __reduce_max_sync(0xffffffffu, k);
    k ^= (k >> 31) & 0x7fffffff;
    return __int_as_float(k);
}
__device__ __forceinline__ float warp_sum(float x) {
#pragma unroll
    for (int o = 16; o > 0; o >>= 1) x += __shfl_xor_sync(0xffffffffu, x, o);
    return x;
}
__device__ __forceinline__ void unpack8(const uint4& v, float* f) {
    f[0] = bf_lo(v.x); f[1] = bf_hi(v.x); f[2] = bf_lo(v.y); f[3] = bf_hi(v.y);
    f[4] = bf_lo(v.z); f[5] = bf_hi(v.z); f[6] = bf_lo(v.w); f[7] = bf_hi(v.w);
}
__device__ __forceinline__ void ln_stats(const uint4& a, const uint4& b, float& mean_bf, float& sd_bf) {
    float f[16];
    unpack8(a, f); unpack8(b, f + 8);
    float s = 0.f;
#pragma unroll
    for (int i = 0; i < 16; i++) s += f[i];
    const float mean = warp_sum(s) * (1.f / DM);
    float q = 0.f;
#pragma unroll
    for (int i = 0; i < 16; i++) { const float d = f[i] - mean; q = fmaf(d, d, q); }
    const float var = warp_sum(q) * (1.f / DM);
    mean_bf = rbf(mean);
    sd_bf = rbf(__fsqrt_rn(rbf(rbf(var) + 1e-5f)));
}
__device__ __forceinline__ float ln_apply(float x, float mean_bf, float sd_bf) {
    return rbf(__fdiv_rn(rbf(x - mean_bf), sd_bf));
}
__device__ __forceinline__ float2 fold8(const float* c) {
    float v[8];
#pragma unroll
    for (int i = 0; i < 8; i++) v[i] = c[2 * i] + c[2 * (i ^ 1) + 1];
    const float w0 = v[0] + __shfl_xor_sync(0xffffffffu, v[2], 1);
    const float w1 = v[1] + __shfl_xor_sync(0xffffffffu, v[3], 1);
    const float w4 = v[4] + __shfl_xor_sync(0xffffffffu, v[6], 1);
    const float w5 = v[5] + __shfl_xor_sync(0xffffffffu, v[7], 1);
    return make_float2(w0 + __shfl_xor_sync(0xffffffffu, w4, 2), w1 + __shfl_xor_sync(0xffffffffu, w5, 2));
}
__device__ __forceinline__ void tensor_load_2d(uint32_t dst, const CUtensorMap* map, int cx, int cy, uint32_t bar) {
    asm volatile("cp.async.bulk.tensor.2d.shared::cluster.global.mbarrier::complete_tx::bytes [%0], [%1, {%2, %3}], [%4];"
                 ::"r"(dst), "l"(map), "r"(cx), "r"(cy), "r"(bar) : "memory");
}
__device__ __forceinline__ void tensor_load_2d_hint(uint32_t dst, const CUtensorMap* map, int cx, int cy, uint32_t bar, uint64_t pol) {
    asm volatile("cp.async.bulk.tensor.2d.shared::cluster.global.mbarrier::complete_tx::bytes.L2::cache_hint [%0], [%1, {%2, %3}], [%4], %5;"
                 ::"r"(dst), "l"(map), "r"(cx), "r"(cy), "r"(bar), "l"(pol) : "memory");
}
__device__ __forceinline__ uint4 lds_v4(uint32_t addr) {
    uint4 v;
    asm volatile("ld.shared.v4.u32 {%0,%1,%2,%3}, [%4];" : "=r"(v.x), "=r"(v.y), "=r"(v.z), "=r"(v.w) : "r"(addr) : "memory");
    return v;
}
__device__ __forceinline__ void sts_u32(uint32_t addr, uint32_t v) {
    asm volatile("st.shared.u32 [%0], %1;" ::"r"(addr), "r"(v) : "memory");
}
__device__ __forceinline__ void contribute(const Params& p, int b, int tid, float2 y) {
    const int n0 = b * DM + (tid >> 5) * 64 + (tid & 3) * 16 + ((tid & 31) >> 2);
    float4* a = p.acc + ((b * 128 + (tid >> 1)) * ACC_STRIDE * 2 + (tid & 1));
    float o0, o1, cnt, z;
    asm volatile("atom.relaxed.gpu.global.add.v4.f32 {%0,%1,%2,%3}, [%4], {%5,%6,%7,%8};"
                 : "=f"(o0), "=f"(o1), "=f"(cnt), "=f"(z) : "l"(a), "f"(y.x), "f"(y.y), "f"(1.f), "f"(0.f) : "memory");
    if (cnt == (float)(NPROD - 1)) {
        p.out[n0] = __float2bfloat16_rn(o0 + y.x);
        p.out[n0 + 8] = __float2bfloat16_rn(o1 + y.y);
        *a = make_float4(0.f, 0.f, 0.f, 0.f);
    }
}

__global__ void __cluster_dims__(2, 1, 1) __launch_bounds__(NTHREADS, 1)
fused_decode_kernel(const __grid_constant__ Params p, const __grid_constant__ Maps maps) {
    extern __shared__ __align__(1024) unsigned char smem[];
    const uint32_t sb = (uint32_t)__cvta_generic_to_shared(smem);
    const uint32_t full0 = sb + OFF_BAR, empty0 = full0 + NST * 8;
    const uint32_t qbar = empty0 + NST * 8, obar = qbar + 8, mlbar = obar + 8;
    const int tid = threadIdx.x, warp = tid >> 5, lane = tid & 31;
    const int cta = blockIdx.x;
    const int g = lane >> 2, c = lane & 3;
    const int r = lane & 7, mi = lane >> 3;
    const bool diag = (c == (g >> 1));

    if (cta < NATT) {
        const int rank = cta & 1, b = (cta >> 1) & 1, h = cta >> 2;
        if (warp == 8) {
            const int row0 = (b * NH + h) * SK + (SK - WIN) + rank * (WIN / 2);
            const char* kp = (const char*)(p.kc + (size_t)row0 * DH);
            uint64_t pol;
            asm volatile("createpolicy.fractional.L2::evict_first.b64 %0, 1.0;" : "=l"(pol));
            if (lane == 0) {
#pragma unroll
                for (int s = 0; s < NST; s++) mbar_init(full0 + 8 * s, 1);
                asm volatile("fence.mbarrier_init.release.cluster;" ::: "memory");
#pragma unroll
                for (int j = 0; j < PRE; j++) {
                    mbar_expect_tx(full0 + 8 * (4 + j), STAGE);
                    bulk_load_hint(sb + (4 + j) * STAGE, kp + j * STAGE, STAGE, full0 + 8 * (4 + j), pol);
                }
#pragma unroll
                for (int s = 0; s < 4; s++) {
                    mbar_expect_tx(full0 + 8 * s, STAGE);
                    tensor_load_2d(sb + s * STAGE, &maps.wq, h * DH, rank * 256 + s * 64, full0 + 8 * s);
                }
#pragma unroll
                for (int j = PRE; j < NST - 4; j++) {
                    mbar_expect_tx(full0 + 8 * (4 + j), STAGE);
                    bulk_load_hint(sb + (4 + j) * STAGE, kp + j * STAGE, STAGE, full0 + 8 * (4 + j), pol);
                }
                TL(1);
#pragma unroll
                for (int s = 0; s < NST; s++) mbar_init(empty0 + 8 * s, 8);
#pragma unroll
                for (int s = 0; s < 3; s++) mbar_init(qbar + 8 * s, 1);
                asm volatile("fence.mbarrier_init.release.cluster;" ::: "memory");
                mbar_expect_tx(qbar, 16 * 512);
                mbar_expect_tx(obar, 512);
                mbar_expect_tx(mlbar, 16 * 8);
                asm volatile("prefetch.tensormap [%0];" ::"l"(&maps.v) : "memory");
            }
            __syncwarp();
            cluster_arrive_relaxed();
            cluster_wait();
            if (lane == 0) {
                const char* wp = (const char*)(p.wo + (size_t)(h * DH + rank * 64) * DM);
                int s = 0, ph = 0;
#pragma unroll 1
                for (int i = NST; i < 72; i++) {
                    mbar_wait(empty0 + 8 * s, ph);
                    mbar_expect_tx(full0 + 8 * s, STAGE);
                    if (i < 36) bulk_load_hint(sb + s * STAGE, kp + (i - 4) * STAGE, STAGE, full0 + 8 * s, pol);
                    else if (i < 40) bulk_load(sb + s * STAGE, wp + (i - 36) * STAGE, STAGE, full0 + 8 * s);
                    else tensor_load_2d_hint(sb + s * STAGE, &maps.v, 0, 2 * row0 + (i - 40) * 128, full0 + 8 * s, pol);
                    if (++s == NST) { s = 0; ph ^= 1; }
                }
                TL(2);
            }
        } else {
            const int grp = warp >> 2, w4 = warp & 3;
            const bool e = g & 1;
            const uint32_t sel0 = e ? 0x1044u : 0x4410u, sel1 = e ? 0x3244u : 0x4432u;
            constexpr float LOG2E = 1.4426950408889634f;
            uint32_t qf[8][2];
            {
                if (tid == 0) TL(0);
                const __nv_bfloat16* xb = p.x + b * DM;
                const uint4 xs0 = ldg_ca(xb + lane * 16), xs1 = ldg_ca(xb + lane * 16 + 8);
                uint32_t xr[4];
#pragma unroll
                for (int i = 0; i < 4; i++) xr[i] = ldg_u16(xb + rank * 256 + (grp + (i & 2)) * 64 + w4 * 16 + (i & 1) * 8 + g);
                cluster_arrive_relaxed();
                float mean_bf, sd_bf;
                ln_stats(xs0, xs1, mean_bf, sd_bf);
                uint32_t xf[2];
#pragma unroll
                for (int t = 0; t < 2; t++)
                    xf[t] = diag ? pack_bf16(ln_apply(bf_lo(xr[2 * t]), mean_bf, sd_bf), ln_apply(bf_lo(xr[2 * t + 1]), mean_bf, sd_bf)) : 0u;
                float o[8][4];
#pragma unroll
                for (int j = 0; j < 8; j++) { o[j][0] = o[j][1] = o[j][2] = o[j][3] = 0.f; }
                if (tid == 0) TL(4);
                cluster_wait();
#pragma unroll
                for (int t = 0; t < 2; t++) {
                    const int s = grp + 2 * t;
                    const uint32_t f0 = __byte_perm(xf[t], 0, sel0), f1 = __byte_perm(xf[t], 0, sel1);
                    const uint32_t vb = sb + s * STAGE + (w4 * 16 + r + 8 * (mi >> 1)) * 256 + (mi & 1) * 128 + r * 16;
                    mbar_wait(full0 + 8 * s, 0);
                    uint32_t a[8][4];
#pragma unroll
                    for (int j = 0; j < 8; j++) ldsm4t(a[j], vb ^ (j << 4));
#pragma unroll
                    for (int j = 0; j < 8; j++) mma16816(o[j], a[j], f0, f1);
                    __syncwarp();
                    if (lane == 0) mbar_arrive2(empty0 + 8 * s);
                }
                float lo[16], hi[16];
#pragma unroll
                for (int j = 0; j < 8; j++) { lo[2 * j] = o[j][0]; lo[2 * j + 1] = o[j][1]; hi[2 * j] = o[j][2]; hi[2 * j + 1] = o[j][3]; }
                const float2 u0 = fold8(lo), u1 = fold8(hi);
                const uint32_t slot = sb + OFF_QPART + (rank * 8 + warp) * 512 + lane * 16;
                st_async_v4(mapa(slot, 0), u0.x, u0.y, u1.x, u1.y, mapa(qbar, 0));
                st_async_v4(mapa(slot, 1), u0.x, u0.y, u1.x, u1.y, mapa(qbar, 1));
                if (tid == 0) TL(5);
                if (tid < 128) {
                    mbar_wait_cluster(qbar, 0);
                    float sum = 0.f;
#pragma unroll
                    for (int i = 0; i < 16; i++) sum += lds_f32(sb + OFF_QPART + i * 512 + tid * 4);
                    const int col = (tid & 2) * 32 + ((tid >> 2) & 3) * 16 + (tid & 1) * 8 + (tid >> 4);
                    sts_u16(sb + OFF_QBF + col * 2, pack_bf16(sum, 0.f));
                }
                bar_sync(1, 256);
#pragma unroll
                for (int j = 0; j < 8; j++) {
                    qf[j][0] = lds_u32(sb + OFF_QBF + ((j ^ g) * 16) + c * 4);
                    qf[j][1] = lds_u32(sb + OFF_QBF + 128 + ((j ^ g) * 16) + c * 4);
                }
                if (tid == 0) TL(6);
            }
            {
                const uint32_t koff = (w4 * 16 + r + 8 * (mi & 1)) * 256 + (mi >> 1) * 128 + r * 16;
                uint32_t sdst = sb + OFF_S + (grp * 64 + w4 * 16 + g) * 2;
                int s = 4 + grp, ph = 0;
#pragma unroll 1
                for (int it = 0; it < 16; it++) {
                    const uint32_t kb = sb + s * STAGE + koff;
                    mbar_wait(full0 + 8 * s, ph);
                    float sa[4] = {0.f, 0.f, 0.f, 0.f}, sc[4] = {0.f, 0.f, 0.f, 0.f};
                    uint32_t a[8][4];
#pragma unroll
                    for (int j = 0; j < 8; j++) ldsm4(a[j], kb ^ (j << 4));
#pragma unroll
                    for (int j = 0; j < 8; j += 2) {
                        mma16816(sa, a[j], qf[j][0], qf[j][1]);
                        mma16816(sc, a[j + 1], qf[j + 1][0], qf[j + 1][1]);
                    }
                    __syncwarp();
                    if (lane == 0) mbar_arrive2(empty0 + 8 * s);
                    uint32_t pk = pack_bf16(e ? sa[1] + sc[1] : sa[0] + sc[0], e ? sa[3] + sc[3] : sa[2] + sc[2]);
                    pk = pack_bf16(bf_lo(pk) * 0.08838834764831845f, bf_hi(pk) * 0.08838834764831845f);
                    if (diag) { sts_u16(sdst, pk); sts_u16(sdst + 16, pk >> 16); }
                    sdst += 256;
                    s += 2;
                    if (s >= NST) { s -= NST; ph ^= 1; }
                }
            }
            if (tid == 224) TL(10);
            {
                __syncwarp();
                const int t = (lane & 30) + grp, hf = lane & 1;
                float sv[8];
                unpack8(lds_v4(sb + OFF_S + (t * 64 + w4 * 16 + hf * 8) * 2), sv);
                float m = sv[0];
#pragma unroll
                for (int i = 1; i < 8; i++) m = fmaxf(m, sv[i]);
                m = warp_max(m);
                float l = 0.f;
#pragma unroll
                for (int i = 0; i < 8; i++) { sv[i] = ex2((sv[i] - m) * LOG2E); l += sv[i]; }
                l = warp_sum(l);
                if (lane < 2) st_async_v2(mapa(sb + OFF_ML + (rank * 8 + warp) * 8, lane), m, l, mapa(mlbar, lane));
                mbar_wait_cluster(mlbar, 0);
                const float2 ml = lds_f32x2(sb + OFF_ML + (lane & 15) * 8);
                const float M = warp_max(ml.x);
                float L = ex2((ml.x - M) * LOG2E) * ml.y;
#pragma unroll
                for (int ofs = 8; ofs > 0; ofs >>= 1) L += __shfl_xor_sync(0xffffffffu, L, ofs);
                const float f = __fdiv_rn(ex2((m - M) * LOG2E), L);
#pragma unroll
                for (int j = 0; j < 4; j++) sts_u32(sb + OFF_P + t * 128 + j * 32 + w4 * 8 + hf * 4, pack_bf16(sv[2 * j] * f, sv[2 * j + 1] * f));
            }
            uint32_t wa[4][4][4];
#pragma unroll
            for (int t = 0; t < 4; t++) {
                const int st = (36 + t) % NST;
                mbar_wait(full0 + 8 * st, ((36 + t) / NST) & 1);
                const uint32_t wb = sb + st * STAGE + (r + 8 * (mi >> 1)) * 1024 + warp * 128 + (((mi & 1) * 4) ^ r ^ (2 * t)) * 16;
#pragma unroll
                for (int j = 0; j < 4; j++) ldsm4t(wa[t][j], wb ^ (j << 4));
                __syncwarp();
                if (lane == 0) mbar_arrive(empty0 + 8 * st);
            }
            bar_sync(1, 256);
            if (tid == 224) TL(11);
            float oa[4] = {0.f, 0.f, 0.f, 0.f}, ob[4] = {0.f, 0.f, 0.f, 0.f};
            {
                const uint32_t voff = (8 * (mi >> 1) + r) * 256 + grp * 128 + ((2 * w4) ^ (mi & 1) ^ (r >> 2) ^ (2 * (r & 3) + grp)) * 16;
                const bool feed = (c >> 1) == (g & 1);
                uint32_t psrc = sb + OFF_P + c * 32;
                int s = 40 % NST, ph = (40 / NST) & 1;
#pragma unroll 1
                for (int it = 0; it < 32; it++) {
                    uint4 p0 = make_uint4(0u, 0u, 0u, 0u), p1 = p0;
                    if (feed) { p0 = lds_v4(psrc); p1 = lds_v4(psrc + 16); }
                    psrc += 128;
                    const uint32_t vb = sb + s * STAGE + voff;
                    mbar_wait(full0 + 8 * s, ph);
                    uint32_t a[4][4];
#pragma unroll
                    for (int j = 0; j < 4; j++) ldsm4t(a[j], vb + j * 4096);
                    mma16816(oa, a[0], p0.x, p0.y);
                    mma16816(ob, a[1], p0.z, p0.w);
                    mma16816(oa, a[2], p1.x, p1.y);
                    mma16816(ob, a[3], p1.z, p1.w);
                    __syncwarp();
                    if (lane == 0) mbar_arrive(empty0 + 8 * s);
                    if (++s == NST) { s = 0; ph ^= 1; }
                }
            }
            if (tid == 224) TL(7);
            if (c == 0)
                st_async_v2(mapa(sb + OFF_OPART + (w4 * 8 + g) * 16 + rank * 8, grp),
                            (oa[0] + oa[3]) + (ob[0] + ob[3]), (oa[1] + oa[2]) + (ob[1] + ob[2]), mapa(obar, grp));
            const int kk = c ^ (g >> 1);
            mbar_wait_cluster(obar, 0);
            if (tid == 224) TL(8);
            const float4 ov = lds_f32x4(sb + OFF_OPART + (kk * 8 + 2 * c + (g & 1)) * 16);
            const uint32_t opk = pack_bf16(ov.x + ov.z, ov.y + ov.w);
            const uint32_t ob0 = __byte_perm(opk, 0, sel0), ob1 = __byte_perm(opk, 0, sel1);
            float y[4][4];
#pragma unroll
            for (int j = 0; j < 4; j++) { y[j][0] = y[j][1] = y[j][2] = y[j][3] = 0.f; }
#pragma unroll
            for (int t = 0; t < 4; t++) {
                const uint32_t f0 = (kk == t) ? ob0 : 0u, f1 = (kk == t) ? ob1 : 0u;
#pragma unroll
                for (int j = 0; j < 4; j++) mma16816(y[j], wa[t][j], f0, f1);
            }
            float yy[16];
#pragma unroll
            for (int j = 0; j < 4; j++) { yy[2 * j] = y[j][0]; yy[2 * j + 1] = y[j][1]; yy[8 + 2 * j] = y[j][2]; yy[8 + 2 * j + 1] = y[j][3]; }
            const float2 yo = fold8(yy);
            if (tid == 224) TL(9);
            contribute(p, b, tid, yo);
            if (tid == 224) TL(3);
        }
    } else {
        const int fj = cta - NATT;
        const int sh1 = fj & 1;
        const int T1 = 32 + sh1, T2 = (fj == NFFN - 1) ? (FF - (NFFN - 1) * FSL) / 16 : FSL / 16;
        if (warp == 8) {
            if (lane == 0) {
                asm volatile("prefetch.tensormap [%0];" ::"l"(&maps.w1) : "memory");
#pragma unroll
                for (int s = 0; s < NST; s++) { mbar_init(full0 + 8 * s, 1); mbar_init(empty0 + 8 * s, 8); }
                asm volatile("fence.mbarrier_init.release.cluster;" ::: "memory");
            }
            __syncwarp();
            bar_sync(3, NTHREADS);
            if (lane == 0) {
                const char* p2 = (const char*)(p.w2 + (size_t)fj * FSL * DM);
                int s = 0, ph = 1;
#pragma unroll 1
                for (int i = 0; i < T1 + T2; i++) {
                    mbar_wait(empty0 + 8 * s, ph);
                    if (i < T1) {
                        mbar_expect_tx(full0 + 8 * s, 16 * FSL * 2);
                        tensor_load_2d(sb + s * STAGE, &maps.w1, fj * (FSL / 2), i * 16 - sh1, full0 + 8 * s);
                    } else {
                        mbar_expect_tx(full0 + 8 * s, STAGE);
                        bulk_load(sb + s * STAGE, p2 + (size_t)(i - T1) * STAGE, STAGE, full0 + 8 * s);
                    }
                    if (++s == NST) { s = 0; ph ^= 1; }
                }
            }
        } else {
            if (tid == 0) TL(0);
            const uint32_t xn_s = sb + OFF_QPART;
            const uint32_t g_s = xn_s + 2 * 1056;
            const uint4 xs0 = ldg_na(p.x + (warp & 1) * DM + lane * 16), xs1 = ldg_na(p.x + (warp & 1) * DM + lane * 16 + 8);
            uint32_t bias_raw[6], res_raw[6];
#pragma unroll
            for (int j = 0; j < 6; j++) bias_raw[j] = ldg_u16(p.b1 + min(fj * FSL + (warp + 8 * (j >> 1)) * 16 + (j & 1) * 8 + g, FF - 1));
#pragma unroll
            for (int j = 0; j < 6; j++) res_raw[j] = ldg_u16((j < 4 ? p.x + (j >> 1) * DM : p.b2) + warp * 64 + c * 16 + (j & 1) * 8 + g);
            bar_sync(3, NTHREADS);
            if (warp < 2) {
                float mean_bf, sd_bf, xn[16];
                ln_stats(xs0, xs1, mean_bf, sd_bf);
                unpack8(xs0, xn); unpack8(xs1, xn + 8);
#pragma unroll
                for (int i = 0; i < 16; i++) sts_u16(xn_s + warp * 1056 + (lane * 16 + i + sh1) * 2, pack_bf16(ln_apply(xn[i], mean_bf, sd_bf), 0.f));
                if (lane < 16) sts_u16(xn_s + warp * 1056 + (lane == 15 && sh1 ? 0 : DM + sh1 + lane) * 2, 0);
            }
            bar_sync(1, 256);
            if (tid == 0) TL(4);
            int s = 0, ph = 0;
            float hacc[3][4];
#pragma unroll
            for (int j = 0; j < 3; j++) { hacc[j][0] = hacc[j][1] = hacc[j][2] = hacc[j][3] = 0.f; }
            uint32_t aoff[3];
#pragma unroll
            for (int j = 0; j < 3; j++) aoff[j] = (r + 8 * (mi >> 1)) * (FSL * 2) + min(2 * (warp + 8 * j) + (mi & 1), FSL / 8 - 1) * 16;
#pragma unroll 1
            for (int i = 0; i < T1; i++) {
                uint32_t f0 = 0, f1 = 0;
                if (g < 2) { f0 = lds_u32(xn_s + g * 1056 + i * 32 + c * 4); f1 = lds_u32(xn_s + g * 1056 + i * 32 + 16 + c * 4); }
                mbar_wait(full0 + 8 * s, ph);
#pragma unroll
                for (int j = 0; j < 3; j++) {
                    uint32_t a[4];
                    ldsm4t(a, sb + s * STAGE + aoff[j]);
                    mma16816(hacc[j], a, f0, f1);
                }
                __syncwarp();
                if (lane == 0) mbar_arrive(empty0 + 8 * s);
                if (++s == NST) { s = 0; ph ^= 1; }
            }
            if (tid == 0) TL(5);
            if (c == 0) {
#pragma unroll
                for (int j = 0; j < 3; j++)
#pragma unroll
                    for (int hf = 0; hf < 2; hf++) {
                        const int f = (warp + 8 * j) * 16 + hf * 8 + g;
                        if (f < FSL) {
                            const float bias = bf_lo(bias_raw[2 * j + hf]);
#pragma unroll
                            for (int bb = 0; bb < 2; bb++) {
                                const float hv = rbf(rbf(hacc[j][2 * hf + bb]) + bias);
                                const float inner = 0.7978845608028654f * (hv + 0.044715f * hv * hv * hv);
                                const float gv = 0.5f * hv * (1.f + tanhf(inner));
                                sts_u16(g_s + bb * 704 + f * 2, pack_bf16(gv, 0.f));
                            }
                        }
                    }
            }
            bar_sync(1, 256);
            if (tid == 0) TL(6);
            float y[2][4][4];
#pragma unroll
            for (int bb = 0; bb < 2; bb++)
#pragma unroll
                for (int j = 0; j < 4; j++) { y[bb][j][0] = y[bb][j][1] = y[bb][j][2] = y[bb][j][3] = 0.f; }
            const int sh = (g & 1) * 16;
#pragma unroll 1
            for (int i = 0; i < T2; i++) {
                uint32_t f[2][2] = {{0u, 0u}, {0u, 0u}};
                if (diag) {
#pragma unroll
                    for (int bb = 0; bb < 2; bb++) {
                        f[bb][0] = lds_u16(g_s + bb * 704 + (i * 16 + g) * 2) << sh;
                        f[bb][1] = lds_u16(g_s + bb * 704 + (i * 16 + 8 + g) * 2) << sh;
                    }
                }
                const uint32_t wb = sb + s * STAGE + (r + 8 * (mi >> 1)) * 1024 + warp * 128 + (((mi & 1) * 4) ^ r) * 16;
                mbar_wait(full0 + 8 * s, ph);
#pragma unroll
                for (int j = 0; j < 4; j++) {
                    uint32_t a[4];
                    ldsm4t(a, wb ^ (j << 4));
                    mma16816(y[0][j], a, f[0][0], f[0][1]);
                    mma16816(y[1][j], a, f[1][0], f[1][1]);
                }
                __syncwarp();
                if (lane == 0) mbar_arrive(empty0 + 8 * s);
                if (++s == NST) { s = 0; ph ^= 1; }
            }
#pragma unroll
            for (int bb = 0; bb < 2; bb++) {
                float yy[16];
#pragma unroll
                for (int j = 0; j < 4; j++) { yy[2 * j] = y[bb][j][0]; yy[2 * j + 1] = y[bb][j][1]; yy[8 + 2 * j] = y[bb][j][2]; yy[8 + 2 * j + 1] = y[bb][j][3]; }
                float2 yo = fold8(yy);
                if (fj == 0) {
                    yo.x += bf_lo(res_raw[2 * bb]) + bf_lo(res_raw[4]);
                    yo.y += bf_lo(res_raw[2 * bb + 1]) + bf_lo(res_raw[5]);
                }
                contribute(p, bb, tid, yo);
            }
            if (tid == 0) TL(3);
        }
    }
}

typedef CUresult (*EncodeFn)(CUtensorMap*, CUtensorMapDataType, cuuint32_t, void*, const cuuint64_t*, const cuuint64_t*,
                             const cuuint32_t*, const cuuint32_t*, CUtensorMapInterleave, CUtensorMapSwizzle,
                             CUtensorMapL2promotion, CUtensorMapFloatOOBfill);

void encode_2d(EncodeFn fn, CUtensorMap* map, CUtensorMapDataType dt, const void* base, uint64_t cols, uint64_t rows,
               uint64_t pitch_bytes, uint32_t box_cols, uint32_t box_rows, CUtensorMapSwizzle sw = CU_TENSOR_MAP_SWIZZLE_NONE) {
    const cuuint64_t dims[2] = {cols, rows}, strides[1] = {pitch_bytes};
    const cuuint32_t box[2] = {box_cols, box_rows}, estr[2] = {1, 1};
    fn(map, dt, 2, const_cast<void*>(base), dims, strides, box, estr, CU_TENSOR_MAP_INTERLEAVE_NONE,
       sw, CU_TENSOR_MAP_L2_PROMOTION_NONE, CU_TENSOR_MAP_FLOAT_OOB_FILL_NONE);
}

}

extern "C" void kernel_launch(void* const* d_in, const int* in_sizes, int n_in, void* d_out, int out_size) {
    (void)in_sizes; (void)n_in; (void)out_size;
    typedef const __nv_bfloat16* P;
    static EncodeFn encode = nullptr;
    static void* acc = nullptr;
    if (!encode) {
        cudaFuncSetAttribute(fused_decode_kernel, cudaFuncAttributeMaxDynamicSharedMemorySize, SMEM_BYTES);
        cudaDriverEntryPointQueryResult st;
        cudaGetDriverEntryPoint("cuTensorMapEncodeTiled", (void**)&encode, cudaEnableDefault, &st);
        cudaGetSymbolAddress(&acc, g_acc);
    }
    Params p;
    p.kc = (P)d_in[1]; p.x = (P)d_in[0]; p.wo = (P)d_in[4];
    p.acc = (float4*)acc; p.out = (__nv_bfloat16*)d_out;
    p.w2 = (P)d_in[8]; p.b1 = (P)d_in[7]; p.b2 = (P)d_in[9];
    p.tl = nullptr;
    Maps maps;
    encode_2d(encode, &maps.wq, CU_TENSOR_MAP_DATA_TYPE_BFLOAT16, d_in[3], NH * DH, DM, NH * DH * 2, DH, 64);
    encode_2d(encode, &maps.v, CU_TENSOR_MAP_DATA_TYPE_BFLOAT16, d_in[2], 64, (uint64_t)2 * 2 * NH * SK, 128, 64, 128,
              CU_TENSOR_MAP_SWIZZLE_128B);
    encode_2d(encode, &maps.w1, CU_TENSOR_MAP_DATA_TYPE_UINT32, d_in[6], FF / 2, DM, FF * 2, FSL / 2, 16);
    fused_decode_kernel<<<NCTA, NTHREADS, SMEM_BYTES>>>(p, maps);
}
```

```cpp
#include <cuda.h>
#include <cuda_runtime.h>
#include <cuda_bf16.h>
#include <stdint.h>

namespace {

constexpr int DM = 512, NH = 32, SK = 16384, WIN = 4096, DH = 128, FF = 1376;
constexpr int NATT = 128, NFFN = 4, NCTA = NATT + NFFN;
constexpr int NPROD = NH + NFFN;
constexpr int FSL = 352;
#define NST 8
#define PRE 2
#define EG 4
#define PFB 8192
#define NACC 4
#define HINT 0
#define ABX 0
#define ABL 0
#define RED_MODE 2
constexpr int STAGE = 16384;
constexpr int NTHREADS = 288;

constexpr int OFF_QPART = NST * STAGE;
constexpr int OFF_S = OFF_QPART, OFF_P = OFF_QPART + 4096;
constexpr int OFF_OPART = OFF_QPART + 8192;
constexpr int OFF_ML = OFF_OPART + 1024;
constexpr int OFF_QBF = OFF_ML + 128;
static_assert(EG <= NST && 72 % NST == 0, "the end-game tiles sit at the top of the ring");
constexpr int OFF_BAR = OFF_QBF + 256;
constexpr int SMEM_BYTES = OFF_BAR + (2 * NST + 3) * 8;

__device__ unsigned long long g_acc[2 * 2 * DM];

struct Params {
    const __nv_bfloat16 *kc, *x;
    unsigned long long* acc;
    __nv_bfloat16* out;
    const __nv_bfloat16 *w2, *b1, *b2;
    unsigned long long* tl;
};
struct Maps {
    alignas(64) CUtensorMap wq, v, wo, w1;
};

#define TL(i)
#define TT(i)

__device__ __forceinline__ void mbar_init(uint32_t bar, uint32_t cnt) {
    asm volatile("mbarrier.init.shared::cta.b64 [%0], %1;" ::"r"(bar), "r"(cnt) : "memory");
}
__device__ __forceinline__ void mbar_expect_tx(uint32_t bar, uint32_t bytes) {
    asm volatile("mbarrier.arrive.expect_tx.shared::cta.b64 _, [%0], %1;" ::"r"(bar), "r"(bytes) : "memory");
}
__device__ __forceinline__ void mbar_arrive2(uint32_t bar) {
    asm volatile("mbarrier.arrive.shared::cta.b64 _, [%0], 2;" ::"r"(bar) : "memory");
}
__device__ __forceinline__ void mbar_arrive(uint32_t bar) {
    asm volatile("mbarrier.arrive.shared::cta.b64 _, [%0];" ::"r"(bar) : "memory");
}
__device__ __forceinline__ bool mbar_try(uint32_t bar, uint32_t parity) {
    uint32_t ok;
    asm volatile(
        "{\n.reg .pred p;\nmbarrier.try_wait.parity.shared::cta.b64 p, [%1], %2;\nselp.u32 %0, 1, 0, p;\n}\n"
        : "=r"(ok) : "r"(bar), "r"(parity) : "memory");
    return ok;
}
__device__ __forceinline__ bool mbar_test(uint32_t bar, uint32_t parity) {
    uint32_t ok;
    asm volatile(
        "{\n.reg .pred p;\nmbarrier.test_wait.parity.shared::cta.b64 p, [%1], %2;\nselp.u32 %0, 1, 0, p;\n}\n"
        : "=r"(ok) : "r"(bar), "r"(parity) : "memory");
    return ok;
}
__device__ __forceinline__ bool mbar_try_hint(uint32_t bar, uint32_t parity, uint32_t ns) {
    uint32_t ok;
    asm volatile(
        "{\n.reg .pred p;\nmbarrier.try_wait.parity.shared::cta.b64 p, [%1], %2, %3;\nselp.u32 %0, 1, 0, p;\n}\n"
        : "=r"(ok) : "r"(bar), "r"(parity), "r"(ns) : "memory");
    return ok;
}
__device__ __forceinline__ bool mbar_try_cluster(uint32_t bar, uint32_t parity) {
    uint32_t ok;
    asm volatile(
        "{\n.reg .pred p;\nmbarrier.try_wait.parity.acquire.cluster.shared::cta.b64 p, [%1], %2;\nselp.u32 %0, 1, 0, p;\n}\n"
        : "=r"(ok) : "r"(bar), "r"(parity) : "memory");
    return ok;
}
constexpr uint32_t SPIN_LIMIT = 1u << 22;
__device__ __forceinline__ void mbar_wait(uint32_t bar, uint32_t parity) {
    uint32_t n = 0;
    while (!mbar_try(bar, parity))
        if (++n > SPIN_LIMIT) __trap();
}
__device__ __forceinline__ void mbar_wait_cluster(uint32_t bar, uint32_t parity) {
    uint32_t n = 0;
    while (!mbar_try_cluster(bar, parity))
        if (++n > SPIN_LIMIT) __trap();
}
__device__ __forceinline__ void bulk_load(uint32_t dst, const void* src, uint32_t bytes, uint32_t bar) {
    asm volatile("cp.async.bulk.shared::cluster.global.mbarrier::complete_tx::bytes [%0], [%1], %2, [%3];"
                 ::"r"(dst), "l"(src), "r"(bytes), "r"(bar) : "memory");
}
__device__ __forceinline__ void bulk_load_hint(uint32_t dst, const void* src, uint32_t bytes, uint32_t bar, uint64_t pol) {
    asm volatile("cp.async.bulk.shared::cluster.global.mbarrier::complete_tx::bytes.L2::cache_hint [%0], [%1], %2, [%3], %4;"
                 ::"r"(dst), "l"(src), "r"(bytes), "r"(bar), "l"(pol) : "memory");
}
__device__ __forceinline__ uint4 ldg_nc(const void* p) {
    uint4 v;
    asm volatile("ld.global.nc.L1::no_allocate.v4.u32 {%0,%1,%2,%3}, [%4];"
                 : "=r"(v.x), "=r"(v.y), "=r"(v.z), "=r"(v.w) : "l"(p));
    return v;
}
__device__ __forceinline__ uint4 ldg_na(const void* p) {
    uint4 v;
    asm volatile("ld.global.L1::no_allocate.v4.u32 {%0,%1,%2,%3}, [%4];"
                 : "=r"(v.x), "=r"(v.y), "=r"(v.z), "=r"(v.w) : "l"(p) : "memory");
    return v;
}
__device__ __forceinline__ uint32_t ldg_u32(const void* p) {
    uint32_t v;
    asm volatile("ld.global.u32 %0, [%1];" : "=r"(v) : "l"(p) : "memory");
    return v;
}
__device__ __forceinline__ uint32_t ldg_u16(const void* p) {
    uint16_t v;
    asm volatile("ld.global.u16 %0, [%1];" : "=h"(v) : "l"(p) : "memory");
    return v;
}
__device__ __forceinline__ uint4 ldg_ca(const void* p) {
    uint4 v;
    asm volatile("ld.global.nc.v4.u32 {%0,%1,%2,%3}, [%4];"
                 : "=r"(v.x), "=r"(v.y), "=r"(v.z), "=r"(v.w) : "l"(p));
    return v;
}
__device__ __forceinline__ void ldsm4(uint32_t (&r)[4], uint32_t addr) {
    asm volatile("ldmatrix.sync.aligned.m8n8.x4.shared.b16 {%0,%1,%2,%3}, [%4];"
                 : "=r"(r[0]), "=r"(r[1]), "=r"(r[2]), "=r"(r[3]) : "r"(addr) : "memory");
}
__device__ __forceinline__ void ldsm4t(uint32_t (&r)[4], uint32_t addr) {
    asm volatile("ldmatrix.sync.aligned.m8n8.x4.trans.shared.b16 {%0,%1,%2,%3}, [%4];"
                 : "=r"(r[0]), "=r"(r[1]), "=r"(r[2]), "=r"(r[3]) : "r"(addr) : "memory");
}
__device__ __forceinline__ void mma16816(float (&d)[4], const uint32_t (&a)[4], uint32_t b0, uint32_t b1) {
    asm volatile(
        "mma.sync.aligned.m16n8k16.row.col.f32.bf16.bf16.f32 {%0,%1,%2,%3}, {%4,%5,%6,%7}, {%8,%9}, {%0,%1,%2,%3};"
        : "+f"(d[0]), "+f"(d[1]), "+f"(d[2]), "+f"(d[3])
        : "r"(a[0]), "r"(a[1]), "r"(a[2]), "r"(a[3]), "r"(b0), "r"(b1));
}
__device__ __forceinline__ uint32_t mapa(uint32_t addr, uint32_t rank) {
    uint32_t r;
    asm("mapa.shared::cluster.u32 %0, %1, %2;" : "=r"(r) : "r"(addr), "r"(rank));
    return r;
}
__device__ __forceinline__ void st_async_v4(uint32_t addr, float a, float b, float c, float d, uint32_t bar) {
    asm volatile("st.async.shared::cluster.mbarrier::complete_tx::bytes.v4.f32 [%0], {%1,%2,%3,%4}, [%5];"
                 ::"r"(addr), "f"(a), "f"(b), "f"(c), "f"(d), "r"(bar) : "memory");
}
__device__ __forceinline__ void st_async_v2(uint32_t addr, float a, float b, uint32_t bar) {
    asm volatile("st.async.shared::cluster.mbarrier::complete_tx::bytes.v2.f32 [%0], {%1,%2}, [%3];"
                 ::"r"(addr), "f"(a), "f"(b), "r"(bar) : "memory");
}
__device__ __forceinline__ float lds_f32(uint32_t addr) {
    float v;
    asm volatile("ld.shared.f32 %0, [%1];" : "=f"(v) : "r"(addr) : "memory");
    return v;
}
__device__ __forceinline__ float2 lds_f32x2(uint32_t addr) {
    float2 v;
    asm volatile("ld.shared.v2.f32 {%0,%1}, [%2];" : "=f"(v.x), "=f"(v.y) : "r"(addr) : "memory");
    return v;
}
__device__ __forceinline__ float4 lds_f32x4(uint32_t addr) {
    float4 v;
    asm volatile("ld.shared.v4.f32 {%0,%1,%2,%3}, [%4];" : "=f"(v.x), "=f"(v.y), "=f"(v.z), "=f"(v.w) : "r"(addr) : "memory");
    return v;
}
__device__ __forceinline__ uint32_t lds_u32(uint32_t addr) {
    uint32_t v;
    asm volatile("ld.shared.u32 %0, [%1];" : "=r"(v) : "r"(addr) : "memory");
    return v;
}
__device__ __forceinline__ uint32_t lds_u16(uint32_t addr) {
    uint16_t v;
    asm volatile("ld.shared.u16 %0, [%1];" : "=h"(v) : "r"(addr) : "memory");
    return v;
}
__device__ __forceinline__ void sts_u16(uint32_t addr, uint32_t v) {
    asm volatile("st.shared.u16 [%0], %1;" ::"r"(addr), "h"((uint16_t)v) : "memory");
}
__device__ __forceinline__ void sts_v4(uint32_t addr, uint32_t a, uint32_t b, uint32_t c, uint32_t d) {
    asm volatile("st.shared.v4.u32 [%0], {%1,%2,%3,%4};" ::"r"(addr), "r"(a), "r"(b), "r"(c), "r"(d) : "memory");
}
__device__ __forceinline__ void sts_f32x2(uint32_t addr, float a, float b) {
    asm volatile("st.shared.v2.f32 [%0], {%1,%2};" ::"r"(addr), "f"(a), "f"(b) : "memory");
}
__device__ __forceinline__ void bar_sync(int id, int n) { asm volatile("bar.sync %0, %1;" ::"r"(id), "r"(n) : "memory"); }
__device__ __forceinline__ void bar_arrive(int id, int n) { asm volatile("bar.arrive %0, %1;" ::"r"(id), "r"(n) : "memory"); }
__device__ __forceinline__ void cluster_arrive_release() { asm volatile("barrier.cluster.arrive.release.aligned;" ::: "memory"); }
__device__ __forceinline__ void cluster_arrive_relaxed() { asm volatile("barrier.cluster.arrive.relaxed.aligned;" ::: "memory"); }
__device__ __forceinline__ void cluster_wait() { asm volatile("barrier.cluster.wait.acquire.aligned;" ::: "memory"); }

__device__ __forceinline__ uint32_t pin(uint32_t v) { return __shfl_sync(0xffffffffu, v, threadIdx.x & 31); }
template <class T> __device__ __forceinline__ T* pin(T* q) {
    const uint64_t v = (uint64_t)q;
    return (T*)(((uint64_t)pin((uint32_t)(v >> 32)) << 32) | pin((uint32_t)v));
}
__device__ __forceinline__ uint32_t pack_bf16(float lo, float hi) {
    uint32_t r;
    asm("cvt.rn.bf16x2.f32 %0, %1, %2;" : "=r"(r) : "f"(hi), "f"(lo));
    return r;
}
__device__ __forceinline__ float bf_lo(uint32_t v) { return __uint_as_float(v << 16); }
__device__ __forceinline__ float bf_hi(uint32_t v) { return __uint_as_float(v & 0xffff0000u); }
__device__ __forceinline__ float rbf(float x) { return bf_lo(pack_bf16(x, 0.f)); }
__device__ __forceinline__ float ex2(float x) {
    float r;
    asm("ex2.approx.ftz.f32 %0, %1;" : "=f"(r) : "f"(x));
    return r;
}
__device__ __forceinline__ float warp_max(float x) {
    int k = __float_as_int(x);
    k ^= (k >> 31) & 0x7fffffff;
    k = __reduce_max_sync(0xffffffffu, k);
    k ^= (k >> 31) & 0x7fffffff;
    return __int_as_float(k);
}
__device__ __forceinline__ float warp_sum(float x) {
#pragma unroll
    for (int o = 16; o > 0; o >>= 1) x += __shfl_xor_sync(0xffffffffu, x, o);
    return x;
}
__device__ __forceinline__ void unpack8(const uint4& v, float* f) {
    f[0] = bf_lo(v.x); f[1] = bf_hi(v.x); f[2] = bf_lo(v.y); f[3] = bf_hi(v.y);
    f[4] = bf_lo(v.z); f[5] = bf_hi(v.z); f[6] = bf_lo(v.w); f[7] = bf_hi(v.w);
}
__device__ __forceinline__ void ln_stats(const uint4& a, const uint4& b, float& mean_bf, float& sd_bf) {
    float f[16];
    unpack8(a, f); unpack8(b, f + 8);
    float s = 0.f;
#pragma unroll
    for (int i = 0; i < 16; i++) s += f[i];
    const float mean = warp_sum(s) * (1.f / DM);
    float q = 0.f;
#pragma unroll
    for (int i = 0; i < 16; i++) { const float d = f[i] - mean; q = fmaf(d, d, q); }
    const float var = warp_sum(q) * (1.f / DM);
    mean_bf = rbf(mean);
    sd_bf = rbf(__fsqrt_rn(rbf(rbf(var) + 1e-5f)));
}
__device__ __forceinline__ float ln_apply(float x, float mean_bf, float sd_bf) {
    return rbf(__fdiv_rn(rbf(x - mean_bf), sd_bf));
}
__device__ __forceinline__ float2 fold8(const float* c) {
    float v[8];
#pragma unroll
    for (int i = 0; i < 8; i++) v[i] = c[2 * i] + c[2 * (i ^ 1) + 1];
    const float w0 = v[0] + __shfl_xor_sync(0xffffffffu, v[2], 1);
    const float w1 = v[1] + __shfl_xor_sync(0xffffffffu, v[3], 1);
    const float w4 = v[4] + __shfl_xor_sync(0xffffffffu, v[6], 1);
    const float w5 = v[5] + __shfl_xor_sync(0xffffffffu, v[7], 1);
    return make_float2(w0 + __shfl_xor_sync(0xffffffffu, w4, 2), w1 + __shfl_xor_sync(0xffffffffu, w5, 2));
}
__device__ __forceinline__ void tensor_load_2d(uint32_t dst, const CUtensorMap* map, int cx, int cy, uint32_t bar) {
    asm volatile("cp.async.bulk.tensor.2d.shared::cluster.global.mbarrier::complete_tx::bytes [%0], [%1, {%2, %3}], [%4];"
                 ::"r"(dst), "l"(map), "r"(cx), "r"(cy), "r"(bar) : "memory");
}
__device__ __forceinline__ void tensor_load_2d_hint(uint32_t dst, const CUtensorMap* map, int cx, int cy, uint32_t bar, uint64_t pol) {
    asm volatile("cp.async.bulk.tensor.2d.shared::cluster.global.mbarrier::complete_tx::bytes.L2::cache_hint [%0], [%1, {%2, %3}], [%4], %5;"
                 ::"r"(dst), "l"(map), "r"(cx), "r"(cy), "r"(bar), "l"(pol) : "memory");
}
__device__ __forceinline__ uint4 lds_v4(uint32_t addr) {
    uint4 v;
    asm volatile("ld.shared.v4.u32 {%0,%1,%2,%3}, [%4];" : "=r"(v.x), "=r"(v.y), "=r"(v.z), "=r"(v.w) : "r"(addr) : "memory");
    return v;
}
__device__ __forceinline__ uint2 lds_v2(uint32_t addr) {
    uint2 v;
    asm volatile("ld.shared.v2.u32 {%0,%1}, [%2];" : "=r"(v.x), "=r"(v.y) : "r"(addr) : "memory");
    return v;
}
__device__ __forceinline__ void sts_u32(uint32_t addr, uint32_t v) {
    asm volatile("st.shared.u32 [%0], %1;" ::"r"(addr), "r"(v) : "memory");
}
__device__ __forceinline__ bool needs_float_path(float asum) {
    const bool huge = __any_sync(0xffffffffu, !(asum < 0x1p46f)), tiny = __all_sync(0xffffffffu, asum < 0x1p22f);
    return huge | tiny;
}
__device__ __noinline__ void finish_flagged(unsigned long long* a, __nv_bfloat16* o, float sum) {
    float side;
    asm volatile("fence.acq_rel.gpu;" ::: "memory");
    asm volatile("atom.relaxed.gpu.global.exch.b32 %0, [%1+8192], 0;" : "=f"(side) : "l"(a) : "memory");
    asm volatile("st.global.u16 [%0], %1;" ::"l"(o), "h"((uint16_t)pack_bf16(sum + side, 0.f)) : "memory");
    asm volatile("st.global.u64 [%0], %1;" ::"l"(a), "l"(0ull) : "memory");
}
__device__ __forceinline__ void add_fixed(unsigned long long* a, __nv_bfloat16* o, float ys) {
    const long long v = __float2ll_rn(ys);
    uint32_t lo, hi;
    asm volatile("{\n.reg .b64 t;\nmov.b64 t, {%3, %4};\natom.relaxed.gpu.global.add.u64 t, [%2], t;\nmov.b64 {%0, %1}, t;\n}"
                 : "=r"(lo), "=r"(hi) : "l"(a), "r"((uint32_t)v), "r"((uint32_t)(v >> 32) + 0x1000000u) : "memory");
    const unsigned long long r = (((unsigned long long)hi << 32) | lo) + (unsigned long long)(v + (1ll << 31) - ((long long)(NPROD - 1) << 56));
    const uint32_t t = (uint32_t)(r >> 32) + 0x800000u;
    const float frac = (float)(int)((uint32_t)r ^ 0x80000000u);
    const uint32_t pk = pack_bf16(fmaf(frac, 0x1p-32f, (float)(int)(r >> 32)), 0.f);
    asm volatile("{\n.reg .pred p;\nsetp.lt.u32 p, %3, 0x1000000;\n@p st.global.u16 [%0], %1;\n@p st.global.u64 [%2], 0;\n}"
                 ::"l"(o), "h"((uint16_t)pk), "l"(a), "r"(t) : "memory");
    if (__builtin_expect((t ^ 0x80000000u) < 0x1000000u, 0))
        finish_flagged(a, o, fmaf(frac, 0x1p-32f, (float)(int)((uint32_t)(r >> 32) ^ 0x80000000u)));
}
__device__ __noinline__ void add_float(unsigned long long* a, __nv_bfloat16* o, float ys) {
    asm volatile("red.relaxed.gpu.global.add.f32 [%0+8192], %1;" ::"l"(a), "f"(ys * 0x1p-32f) : "memory");
    asm volatile("red.release.gpu.global.or.b64 [%0], %1;" ::"l"(a), "l"(1ull << 63) : "memory");
    add_fixed(a, o, 0.f);
}
__device__ __forceinline__ void contribute(unsigned long long* a, __nv_bfloat16* o, float ys, bool float_path) {
    if (__builtin_expect(!float_path, 1)) add_fixed(a, o, ys);
    else add_float(a, o, ys);
}

__global__ void __cluster_dims__(2, 1, 1) __launch_bounds__(NTHREADS, 1)
fused_decode_kernel(const __grid_constant__ Params p, const __grid_constant__ Maps maps) {
    extern __shared__ __align__(1024) unsigned char smem[];
    const uint32_t sb = (uint32_t)__cvta_generic_to_shared(smem);
    const uint32_t full0 = sb + OFF_BAR, empty0 = full0 + NST * 8;
    const uint32_t qbar = empty0 + NST * 8, obar = qbar + 8, mlbar = obar + 8;
    const int tid = threadIdx.x, warp = tid >> 5, lane = tid & 31;
    const int cta = blockIdx.x;
    const int g = lane >> 2, c = lane & 3;
    const int r = lane & 7, mi = lane >> 3;
    const bool diag = (c == (g >> 1));

    if (cta < NATT) {
        const int rank = cta & 1, b = (cta >> 1) & 1, h = cta >> 2;
        if (warp == 8) {
            const int row0 = (b * NH + h) * SK + (SK - WIN) + rank * 64;
            const char* kp = (const char*)(p.kc + (size_t)row0 * DH);
            uint64_t pol;
            asm volatile("createpolicy.fractional.L2::evict_first.b64 %0, 1.0;" : "=l"(pol));
            if (lane == 0) {
                asm volatile("cp.async.bulk.prefetch.L2.global.L2::cache_hint [%0], %1, %2;" ::"l"(kp), "r"(PFB), "l"(pol) : "memory");
#pragma unroll
                for (int s = 0; s < NST; s++) mbar_init(full0 + 8 * s, 1);
                asm volatile("fence.mbarrier_init.release.cluster;" ::: "memory");
#pragma unroll
                for (int j = 0; j < PRE; j++) {
                    mbar_expect_tx(full0 + 8 * (4 + j), STAGE);
                    bulk_load_hint(sb + (4 + j) * STAGE, kp + j * (2 * STAGE), STAGE, full0 + 8 * (4 + j), pol);
                }
#pragma unroll
                for (int s = 0; s < 4; s++) {
                    mbar_expect_tx(full0 + 8 * s, STAGE);
                    tensor_load_2d(sb + s * STAGE, &maps.wq, h * DH, rank * 256 + s * 64, full0 + 8 * s);
                }
#pragma unroll
                for (int j = PRE; j < NST - 4; j++) {
                    mbar_expect_tx(full0 + 8 * (4 + j), STAGE);
                    bulk_load_hint(sb + (4 + j) * STAGE, kp + j * (2 * STAGE), STAGE, full0 + 8 * (4 + j), pol);
                }
                TL(1);
#pragma unroll
                for (int s = 0; s < NST; s++) mbar_init(empty0 + 8 * s, 8);
#pragma unroll
                for (int s = 0; s < 3; s++) mbar_init(qbar + 8 * s, 1);
                asm volatile("fence.mbarrier_init.release.cluster;" ::: "memory");
                mbar_expect_tx(qbar, 16 * 512);
                mbar_expect_tx(obar, 1024);
                mbar_expect_tx(mlbar, 16 * 8);
                asm volatile("prefetch.tensormap [%0];" ::"l"(&maps.wo) : "memory");
                asm volatile("prefetch.tensormap [%0];" ::"l"(&maps.v) : "memory");
            }
            __syncwarp();
            cluster_arrive_relaxed();
            cluster_wait();
            if (lane == 0) {
                int s = 0, ph = 0;
#pragma unroll 1
                for (int i = NST; i < 72; i++) {
                    mbar_wait(empty0 + 8 * s, ph);
                    mbar_expect_tx(full0 + 8 * s, STAGE);
                    if (i < 36) bulk_load_hint(sb + s * STAGE, kp + (i - 4) * (2 * STAGE), STAGE, full0 + 8 * s, pol);
                    else if (i < 40) tensor_load_2d(sb + s * STAGE, &maps.wo, rank * 256 + (i - 36) * 64, h * DH, full0 + 8 * s);
                    else tensor_load_2d_hint(sb + s * STAGE, &maps.v, 0, 2 * row0 + (i - 40) * 256, full0 + 8 * s, pol);
                    if (++s == NST) { s = 0; ph ^= 1; }
                }
                TL(2);
            }
        } else {
            const int grp = warp >> 2, w4 = warp & 3;
            const bool e = g & 1;
            const uint32_t sel0 = e ? 0x1044u : 0x4410u, sel1 = e ? 0x3244u : 0x4432u;
            constexpr float LOG2E = 1.4426950408889634f;
            uint32_t qf[8][2];
            {
                if (tid == 0) TL(0);
                const __nv_bfloat16* xb = p.x + b * DM;
                const uint4 xs0 = ldg_ca(xb + lane * 16), xs1 = ldg_ca(xb + lane * 16 + 8);
                uint32_t xr[4];
#pragma unroll
                for (int i = 0; i < 4; i++) xr[i] = ldg_u16(xb + rank * 256 + (grp + (i & 2)) * 64 + w4 * 16 + (i & 1) * 8 + g);
                cluster_arrive_relaxed();
                float mean_bf, sd_bf;
                ln_stats(xs0, xs1, mean_bf, sd_bf);
                uint32_t xf[2];
#pragma unroll
                for (int t = 0; t < 2; t++)
                    xf[t] = diag ? pack_bf16(ln_apply(bf_lo(xr[2 * t]), mean_bf, sd_bf), ln_apply(bf_lo(xr[2 * t + 1]), mean_bf, sd_bf)) : 0u;
                float o[8][4];
#pragma unroll
                for (int j = 0; j < 8; j++) { o[j][0] = o[j][1] = o[j][2] = o[j][3] = 0.f; }
                if (tid == 0) TL(4);
                cluster_wait();
#pragma unroll
                for (int t = 0; t < 2; t++) {
                    const int s = grp + 2 * t;
                    const uint32_t f0 = __byte_perm(xf[t], 0, sel0), f1 = __byte_perm(xf[t], 0, sel1);
                    const uint32_t vb = sb + s * STAGE + (w4 * 16 + r + 8 * (mi >> 1)) * 256 + (mi & 1) * 128 + r * 16;
                    mbar_wait(full0 + 8 * s, 0);
                    uint32_t a[8][4];
#pragma unroll
                    for (int j = 0; j < 8; j++) ldsm4t(a[j], vb ^ (j << 4));
#pragma unroll
                    for (int j = 0; j < 8; j++) mma16816(o[j], a[j], f0, f1);
                    __syncwarp();
                    if (lane == 0) mbar_arrive2(empty0 + 8 * s);
                }
                float lo[16], hi[16];
#pragma unroll
                for (int j = 0; j < 8; j++) { lo[2 * j] = o[j][0]; lo[2 * j + 1] = o[j][1]; hi[2 * j] = o[j][2]; hi[2 * j + 1] = o[j][3]; }
                const float2 u0 = fold8(lo), u1 = fold8(hi);
                const uint32_t slot = sb + OFF_QPART + (rank * 8 + warp) * 512 + lane * 16;
                st_async_v4(mapa(slot, 0), u0.x, u0.y, u1.x, u1.y, mapa(qbar, 0));
                st_async_v4(mapa(slot, 1), u0.x, u0.y, u1.x, u1.y, mapa(qbar, 1));
                if (tid == 0) TL(5);
                if (tid < 128) {
                    if (!(ABX & 1)) mbar_wait_cluster(qbar, 0);
                    float sum = 0.f;
#pragma unroll
                    for (int i = 0; i < 16; i++) sum += lds_f32(sb + OFF_QPART + i * 512 + tid * 4);
                    const int col = (tid & 2) * 32 + ((tid >> 2) & 3) * 16 + (tid & 1) * 8 + (tid >> 4);
                    sts_u16(sb + OFF_QBF + col * 2, pack_bf16(sum, 0.f));
                }
                bar_sync(1, 256);
#pragma unroll
                for (int j = 0; j < 8; j++) {
                    qf[j][0] = lds_u32(sb + OFF_QBF + ((j ^ g) * 16) + c * 4);
                    qf[j][1] = lds_u32(sb + OFF_QBF + 128 + ((j ^ g) * 16) + c * 4);
                }
                if (tid == 0) TL(6);
            }
            {
                const uint32_t koff = (w4 * 16 + r + 8 * (mi & 1)) * 256 + (mi >> 1) * 128 + r * 16;
                uint32_t sdst = sb + OFF_S + (grp * 64 + w4 * 16 + g) * 2;
                int s = 4 + grp, ph = 0;
#pragma unroll 1
                for (int it = 0; it < 16; it++) {
                    const uint32_t kb = sb + s * STAGE + koff;
                    mbar_wait(full0 + 8 * s, ph);
                    float sa[4] = {0.f, 0.f, 0.f, 0.f}, sc[4] = {0.f, 0.f, 0.f, 0.f};
                    uint32_t a[8][4];
#pragma unroll
                    for (int j = 0; j < 8; j++) ldsm4(a[j], kb ^ (j << 4));
#pragma unroll
                    for (int j = 0; j < 8; j += 2) {
                        mma16816(sa, a[j], qf[j][0], qf[j][1]);
                        mma16816(sc, a[j + 1], qf[j + 1][0], qf[j + 1][1]);
                    }
                    __syncwarp();
                    if (lane == 0) mbar_arrive2(empty0 + 8 * s);
                    uint32_t pk = pack_bf16(e ? sa[1] + sc[1] : sa[0] + sc[0], e ? sa[3] + sc[3] : sa[2] + sc[2]);
                    pk = pack_bf16(bf_lo(pk) * 0.08838834764831845f, bf_hi(pk) * 0.08838834764831845f);
                    if (diag) { sts_u16(sdst, pk); sts_u16(sdst + 16, pk >> 16); }
                    sdst += 256;
                    s += 2;
                    if (s >= NST) { s -= NST; ph ^= 1; }
                }
            }
            if (tid == 224) TL(10);
            {
                __syncwarp();
                const int t = (lane & 30) + grp, hf = lane & 1;
                float sv[8];
                unpack8(lds_v4(sb + OFF_S + (t * 64 + w4 * 16 + hf * 8) * 2), sv);
                float m = sv[0];
#pragma unroll
                for (int i = 1; i < 8; i++) m = fmaxf(m, sv[i]);
                m = warp_max(m);
                float l = 0.f;
#pragma unroll
                for (int i = 0; i < 8; i++) { sv[i] = ex2((sv[i] - m) * LOG2E); l += sv[i]; }
                l = warp_sum(l);
                if (lane < 2) st_async_v2(mapa(sb + OFF_ML + (rank * 8 + warp) * 8, lane), m, l, mapa(mlbar, lane));
                if (!(ABX & 2)) mbar_wait_cluster(mlbar, 0); else bar_sync(1, 256);
                const float2 ml = lds_f32x2(sb + OFF_ML + (lane & 15) * 8);
                const float M = warp_max(ml.x);
                float L = ex2((ml.x - M) * LOG2E) * ml.y;
#pragma unroll
                for (int ofs = 8; ofs > 0; ofs >>= 1) L += __shfl_xor_sync(0xffffffffu, L, ofs);
                const float f = __fdiv_rn(ex2((m - M) * LOG2E), L) * 0x1p32f;
#pragma unroll
                for (int j = 0; j < 4; j++) sts_u32(sb + OFF_P + t * 128 + j * 32 + w4 * 8 + hf * 4, pack_bf16(sv[2 * j] * f, sv[2 * j + 1] * f));
            }
            uint32_t wa[8][2][4];
            {
                const int t4 = 36 + (warp >> 1), st = t4 % NST;
                mbar_wait(full0 + 8 * st, (t4 / NST) & 1);
                const uint32_t wb = sb + st * STAGE + (r + 8 * (mi >> 1)) * 128 + ((4 * (warp & 1) + (mi & 1)) ^ r) * 16;
#pragma unroll
                for (int t = 0; t < 8; t++)
#pragma unroll
                    for (int j = 0; j < 2; j++) ldsm4t(wa[t][j], (wb ^ (((2 * j) ^ (t >> 1)) << 4)) + t * 2048);
                __syncwarp();
                if (lane == 0) asm volatile("mbarrier.arrive.shared::cta.b64 _, [%0], 4;" ::"r"(empty0 + 8 * st) : "memory");
            }
            const uint32_t vbase = pin(sb + (8 * (mi >> 1) + r) * 256 + grp * 128 + ((2 * w4) ^ (mi & 1) ^ (r >> 2) ^ (2 * (r & 3) + grp)) * 16);
            const uint32_t o_dst = pin(mapa(sb + OFF_OPART + rank * 512 + (warp * 8 + g) * 8, c & 1)), o_bar = pin(mapa(obar, c & 1));
            const uint32_t o_src = pin(sb + OFF_OPART + lane * 16);
            uint32_t omask[8];
#pragma unroll
            for (int t = 0; t < 8; t++) omask[t] = pin(g == t ? 0xffffffffu : 0u);
            unsigned long long* const acc_p = pin(p.acc + b * DM + rank * 256 + tid);
            __nv_bfloat16* const out_p = pin(p.out + b * DM + rank * 256 + warp * 32 + c * 8 + g);
            const bool feed = pin((uint32_t)((c >> 1) == (g & 1))), send = pin((uint32_t)(c < 2));
            bar_sync(1, 256);
            if (tid == 224) TL(11);
            float oc[4][4];
#pragma unroll
            for (int j = 0; j < 4; j++) { oc[j][0] = oc[j][1] = oc[j][2] = oc[j][3] = 0.f; }
            {
                auto pv_tile = [&](uint32_t vb, const uint4& p0, const uint4& p1) {
                    uint32_t a[4][4];
#pragma unroll
                    for (int j = 0; j < 4; j++) ldsm4t(a[j], vb + j * 4096);
                    mma16816(oc[0], a[0], p0.x, p0.y);
                    mma16816(oc[1], a[1], p0.z, p0.w);
                    mma16816(oc[NACC == 4 ? 2 : 0], a[2], p1.x, p1.y);
                    mma16816(oc[NACC == 4 ? 3 : 1], a[3], p1.z, p1.w);
                };
                uint32_t psrc = sb + OFF_P + c * 32;
                uint4 pe[EG + 1][2];
#pragma unroll
                for (int j = 0; j < EG; j++) {
                    pe[j][0] = pe[j][1] = make_uint4(0u, 0u, 0u, 0u);
                    if (feed) { pe[j][0] = lds_v4(psrc + (32 - EG + j) * 128); pe[j][1] = lds_v4(psrc + (32 - EG + j) * 128 + 16); }
                }
                int s = 40 % NST, ph = (40 / NST) & 1;
#pragma unroll 1
                for (int it = 0; it < 32 - EG; it++) {
                    uint4 p0 = make_uint4(0u, 0u, 0u, 0u), p1 = p0;
                    if (feed) { p0 = lds_v4(psrc); p1 = lds_v4(psrc + 16); }
                    psrc += 128;
                    mbar_wait(full0 + 8 * s, ph);
                    if (!(ABX & 4)) pv_tile(vbase + s * STAGE, p0, p1);
                    __syncwarp();
                    if (lane == 0) mbar_arrive(empty0 + 8 * s);
                    if (++s == NST) { s = 0; ph ^= 1; }
                }
                constexpr int PH = (72 / NST - 1) & 1;
                bool done[EG + 1];
#pragma unroll
                for (int j = 0; j < EG; j++) done[j] = false;
#pragma unroll
                for (int j = 0; j < EG; j++) {
                    const uint32_t bar = full0 + 8 * (NST - EG + j);
                    if (!done[j]) {
                        if (j == EG - 1) {
                            mbar_wait(bar, PH);
                        } else {
                            uint32_t n = 0;
                            while (!(HINT ? mbar_try_hint(bar, PH, HINT) : mbar_test(bar, PH))) {
#pragma unroll
                                for (int k = j + 1; k < EG; k++)
                                    if (!done[k] && mbar_test(full0 + 8 * (NST - EG + k), PH)) {
                                        done[k] = true;
                                        pv_tile(vbase + (NST - EG + k) * STAGE, pe[k][0], pe[k][1]);
                                    }
                                if (++n > SPIN_LIMIT) __trap();
                            }
                        }
                        pv_tile(vbase + (NST - EG + j) * STAGE, pe[j][0], pe[j][1]);
                    }
                }
            }
            const float oa0 = NACC == 4 ? ((oc[0][0] + oc[0][3]) + (oc[1][0] + oc[1][3])) + ((oc[2][0] + oc[2][3]) + (oc[3][0] + oc[3][3]))
                                        : (oc[0][0] + oc[0][3]) + (oc[1][0] + oc[1][3]);
            const float oa1 = NACC == 4 ? ((oc[0][1] + oc[0][2]) + (oc[1][1] + oc[1][2])) + ((oc[2][1] + oc[2][2]) + (oc[3][1] + oc[3][2]))
                                        : (oc[0][1] + oc[0][2]) + (oc[1][1] + oc[1][2]);
            if (tid == 224) TL(7);
            if (send) st_async_v2(o_dst, oa0, oa1, o_bar);
            mbar_wait(obar, 0);
            if (tid == 224) TL(8);
            const float4 u = lds_f32x4(o_src), v = lds_f32x4(o_src + 512);
            const uint32_t f0 = pack_bf16(u.x + v.x, u.z + v.z), f1 = pack_bf16(u.y + v.y, u.w + v.w);
            float y[2][2][4];
#pragma unroll
            for (int j = 0; j < 4; j++) { y[j >> 1][j & 1][0] = y[j >> 1][j & 1][1] = y[j >> 1][j & 1][2] = y[j >> 1][j & 1][3] = 0.f; }
#pragma unroll
            for (int t = 0; t < 8; t++) {
                mma16816(y[t & 1][1], wa[t][1], f0 & omask[t], f1 & omask[t]);
                mma16816(y[t & 1][0], wa[t][0], f0 & omask[t], f1 & omask[t]);
            }
            const float v3 = y[0][1][2] + y[1][1][3], v2 = y[0][1][0] + y[1][1][1];
            const float v1 = y[0][0][2] + y[1][0][3], v0 = y[0][0][0] + y[1][0][1];
            const float w2 = v2 + __shfl_xor_sync(0xffffffffu, v3, 1);
            const float w0 = v0 + __shfl_xor_sync(0xffffffffu, v1, 1);
            const float x2 = __shfl_xor_sync(0xffffffffu, w2, 2);
            const bool fp = needs_float_path((fabsf(v0) + fabsf(v1)) + (fabsf(v2) + fabsf(v3)));
            const float yo = w0 + x2;
            if (tid == 224) TL(9);
            contribute(acc_p, out_p, yo, fp);
            if (tid == 224) TL(3);
        }
    } else {
        const int fj = cta - NATT;
        const int sh1 = fj & 1;
        const int T1 = 32 + sh1, T2 = (fj == NFFN - 1) ? (FF - (NFFN - 1) * FSL) / 16 : FSL / 16;
        if (warp == 8) {
            if (lane == 0) {
                asm volatile("prefetch.tensormap [%0];" ::"l"(&maps.w1) : "memory");
#pragma unroll
                for (int s = 0; s < NST; s++) { mbar_init(full0 + 8 * s, 1); mbar_init(empty0 + 8 * s, 8); }
                asm volatile("fence.mbarrier_init.release.cluster;" ::: "memory");
            }
            __syncwarp();
            bar_sync(3, NTHREADS);
            if (lane == 0) {
                const char* p2 = (const char*)(p.w2 + (size_t)fj * FSL * DM);
                int s = 0, ph = 1;
#pragma unroll 1
                for (int i = 0; i < T1 + T2; i++) {
                    mbar_wait(empty0 + 8 * s, ph);
                    if (i < T1) {
                        mbar_expect_tx(full0 + 8 * s, 16 * FSL * 2);
                        tensor_load_2d(sb + s * STAGE, &maps.w1, fj * (FSL / 2), i * 16 - sh1, full0 + 8 * s);
                    } else {
                        mbar_expect_tx(full0 + 8 * s, STAGE);
                        bulk_load(sb + s * STAGE, p2 + (size_t)(i - T1) * STAGE, STAGE, full0 + 8 * s);
                    }
                    if (++s == NST) { s = 0; ph ^= 1; }
                }
            }
        } else {
            if (tid == 0) TL(0);
            const uint32_t xn_s = sb + OFF_QPART;
            const uint32_t g_s = xn_s + 2 * 1056;
            const uint4 xs0 = ldg_na(p.x + (warp & 1) * DM + lane * 16), xs1 = ldg_na(p.x + (warp & 1) * DM + lane * 16 + 8);
            uint32_t bias_raw[6], res_raw[6];
#pragma unroll
            for (int j = 0; j < 6; j++) bias_raw[j] = ldg_u16(p.b1 + min(fj * FSL + (warp + 8 * (j >> 1)) * 16 + (j & 1) * 8 + g, FF - 1));
#pragma unroll
            for (int j = 0; j < 6; j++) res_raw[j] = ldg_u16((j < 4 ? p.x + (j >> 1) * DM : p.b2) + warp * 64 + c * 16 + (j & 1) * 8 + g);
            bar_sync(3, NTHREADS);
            if (warp < 2) {
                float mean_bf, sd_bf, xn[16];
                ln_stats(xs0, xs1, mean_bf, sd_bf);
                unpack8(xs0, xn); unpack8(xs1, xn + 8);
#pragma unroll
                for (int i = 0; i < 16; i++) sts_u16(xn_s + warp * 1056 + (lane * 16 + i + sh1) * 2, pack_bf16(ln_apply(xn[i], mean_bf, sd_bf), 0.f));
                if (lane < 16) sts_u16(xn_s + warp * 1056 + (lane == 15 && sh1 ? 0 : DM + sh1 + lane) * 2, 0);
            }
            bar_sync(1, 256);
            if (tid == 0) TL(4);
            int s = 0, ph = 0;
            float hacc[3][4];
#pragma unroll
            for (int j = 0; j < 3; j++) { hacc[j][0] = hacc[j][1] = hacc[j][2] = hacc[j][3] = 0.f; }
            uint32_t aoff[3];
#pragma unroll
            for (int j = 0; j < 3; j++) aoff[j] = (r + 8 * (mi >> 1)) * (FSL * 2) + min(2 * (warp + 8 * j) + (mi & 1), FSL / 8 - 1) * 16;
#pragma unroll 1
            for (int i = 0; i < T1; i++) {
                uint32_t f0 = 0, f1 = 0;
                if (g < 2) { f0 = lds_u32(xn_s + g * 1056 + i * 32 + c * 4); f1 = lds_u32(xn_s + g * 1056 + i * 32 + 16 + c * 4); }
                mbar_wait(full0 + 8 * s, ph);
#pragma unroll
                for (int j = 0; j < 3; j++) {
                    uint32_t a[4];
                    ldsm4t(a, sb + s * STAGE + aoff[j]);
                    mma16816(hacc[j], a, f0, f1);
                }
                __syncwarp();
                if (lane == 0) mbar_arrive(empty0 + 8 * s);
                if (++s == NST) { s = 0; ph ^= 1; }
            }
            if (tid == 0) TL(5);
            if (c == 0) {
#pragma unroll
                for (int j = 0; j < 3; j++)
#pragma unroll
                    for (int hf = 0; hf < 2; hf++) {
                        const int f = (warp + 8 * j) * 16 + hf * 8 + g;
                        if (f < FSL) {
                            const float bias = bf_lo(bias_raw[2 * j + hf]);
#pragma unroll
                            for (int bb = 0; bb < 2; bb++) {
                                const float hv = rbf(rbf(hacc[j][2 * hf + bb]) + bias);
                                const float inner = 0.7978845608028654f * (hv + 0.044715f * hv * hv * hv);
                                const float gv = 0.5f * hv * (1.f + tanhf(inner));
                                sts_u16(g_s + bb * 704 + f * 2, pack_bf16(gv, 0.f));
                            }
                        }
                    }
            }
            bar_sync(1, 256);
            if (tid == 0) TL(6);
            float y[2][4][4];
#pragma unroll
            for (int bb = 0; bb < 2; bb++)
#pragma unroll
                for (int j = 0; j < 4; j++) { y[bb][j][0] = y[bb][j][1] = y[bb][j][2] = y[bb][j][3] = 0.f; }
            const int sh = (g & 1) * 16;
#pragma unroll 1
            for (int i = 0; i < T2; i++) {
                uint32_t f[2][2] = {{0u, 0u}, {0u, 0u}};
                if (diag) {
#pragma unroll
                    for (int bb = 0; bb < 2; bb++) {
                        f[bb][0] = lds_u16(g_s + bb * 704 + (i * 16 + g) * 2) << sh;
                        f[bb][1] = lds_u16(g_s + bb * 704 + (i * 16 + 8 + g) * 2) << sh;
                    }
                }
                const uint32_t wb = sb + s * STAGE + (r + 8 * (mi >> 1)) * 1024 + warp * 128 + (((mi & 1) * 4) ^ r) * 16;
                mbar_wait(full0 + 8 * s, ph);
#pragma unroll
                for (int j = 0; j < 4; j++) {
                    uint32_t a[4];
                    ldsm4t(a, wb ^ (j << 4));
                    mma16816(y[0][j], a, f[0][0], f[0][1]);
                    mma16816(y[1][j], a, f[1][0], f[1][1]);
                }
                __syncwarp();
                if (lane == 0) mbar_arrive(empty0 + 8 * s);
                if (++s == NST) { s = 0; ph ^= 1; }
            }
#pragma unroll
            for (int bb = 0; bb < 2; bb++) {
                float yy[16];
#pragma unroll
                for (int j = 0; j < 4; j++) { yy[2 * j] = y[bb][j][0]; yy[2 * j + 1] = y[bb][j][1]; yy[8 + 2 * j] = y[bb][j][2]; yy[8 + 2 * j + 1] = y[bb][j][3]; }
                float2 yo = fold8(yy);
                if (fj == 0) {
                    yo.x += bf_lo(res_raw[2 * bb]) + bf_lo(res_raw[4]);
                    yo.y += bf_lo(res_raw[2 * bb + 1]) + bf_lo(res_raw[5]);
                }
                const int n0 = bb * DM + warp * 64 + c * 16;
                unsigned long long* a = p.acc + (n0 & ~31) + 4 * g + 2 * (c & 1);
                if (!(ABX & 8) || yo.x == 1234.5f) {
                const bool fp = needs_float_path((fabsf(yo.x) + fabsf(yo.y)) * 0x1p32f);
                contribute(a, p.out + n0 + g, yo.x * 0x1p32f, fp);
                contribute(a + 1, p.out + n0 + 8 + g, yo.y * 0x1p32f, fp);
                }
            }
            if (tid == 0) TL(3);
        }
    }
}

typedef CUresult (*EncodeFn)(CUtensorMap*, CUtensorMapDataType, cuuint32_t, void*, const cuuint64_t*, const cuuint64_t*,
                             const cuuint32_t*, const cuuint32_t*, CUtensorMapInterleave, CUtensorMapSwizzle,
                             CUtensorMapL2promotion, CUtensorMapFloatOOBfill);

void encode_2d(EncodeFn fn, CUtensorMap* map, CUtensorMapDataType dt, const void* base, uint64_t cols, uint64_t rows,
               uint64_t pitch_bytes, uint32_t box_cols, uint32_t box_rows, CUtensorMapSwizzle sw = CU_TENSOR_MAP_SWIZZLE_NONE) {
    const cuuint64_t dims[2] = {cols, rows}, strides[1] = {pitch_bytes};
    const cuuint32_t box[2] = {box_cols, box_rows}, estr[2] = {1, 1};
    fn(map, dt, 2, const_cast<void*>(base), dims, strides, box, estr, CU_TENSOR_MAP_INTERLEAVE_NONE,
       sw, CU_TENSOR_MAP_L2_PROMOTION_NONE, CU_TENSOR_MAP_FLOAT_OOB_FILL_NONE);
}

}

extern "C" void kernel_launch(void* const* d_in, const int* in_sizes, int n_in, void* d_out, int out_size) {
    (void)in_sizes; (void)n_in; (void)out_size;
    typedef const __nv_bfloat16* P;
    static EncodeFn encode = nullptr;
    static void* acc = nullptr;
    if (!encode) {
        cudaFuncSetAttribute(fused_decode_kernel, cudaFuncAttributeMaxDynamicSharedMemorySize, SMEM_BYTES);
        cudaDriverEntryPointQueryResult st;
        cudaGetDriverEntryPoint("cuTensorMapEncodeTiled", (void**)&encode, cudaEnableDefault, &st);
        cudaGetSymbolAddress(&acc, g_acc);
    }
    Params p;
    p.kc = (P)d_in[1]; p.x = (P)d_in[0];
    p.acc = (unsigned long long*)acc; p.out = (__nv_bfloat16*)d_out;
    p.w2 = (P)d_in[8]; p.b1 = (P)d_in[7]; p.b2 = (P)d_in[9];
    p.tl = nullptr;
    Maps maps;
    encode_2d(encode, &maps.wq, CU_TENSOR_MAP_DATA_TYPE_BFLOAT16, d_in[3], NH * DH, DM, NH * DH * 2, DH, 64);
    encode_2d(encode, &maps.v, CU_TENSOR_MAP_DATA_TYPE_BFLOAT16, d_in[2], 64, (uint64_t)2 * 2 * NH * SK, 128, 64, 128,
              CU_TENSOR_MAP_SWIZZLE_128B);
    encode_2d(encode, &maps.wo, CU_TENSOR_MAP_DATA_TYPE_BFLOAT16, d_in[4], DM, NH * DH, DM * 2, 64, 128,
              CU_TENSOR_MAP_SWIZZLE_128B);
    encode_2d(encode, &maps.w1, CU_TENSOR_MAP_DATA_TYPE_UINT32, d_in[6], FF / 2, DM, FF * 2, FSL / 2, 16);
    fused_decode_kernel<<<NCTA, NTHREADS, SMEM_BYTES>>>(p, maps);
}
```

```cpp
#include <cuda.h>
#include <cuda_runtime.h>
#include <cuda_bf16.h>
#include <stdint.h>

namespace {

constexpr int DM = 512, NH = 32, SK = 16384, WIN = 4096, DH = 128, FF = 1376;
constexpr int NATT = 128, NFFN = 4, NCTA = NATT + NFFN;
constexpr int NPROD = NH + NFFN;
constexpr int FSL = 352;
constexpr int NST = 8;
constexpr int STAGE = 16384;
constexpr int PRE = 2;
constexpr int EG = 4;
constexpr int NTHREADS = 288;
static_assert(NST % 2 == 0 && 72 % NST == 0 && EG <= NST, "ring geometry");

constexpr int OFF_QPART = NST * STAGE;
constexpr int OFF_S = OFF_QPART, OFF_P = OFF_QPART + 4096;
constexpr int OFF_OPART = OFF_QPART + 8192;
constexpr int OFF_ML = OFF_OPART + 1024;
constexpr int OFF_QBF = OFF_ML + 128;
constexpr int OFF_BAR = OFF_QBF + 256;
constexpr int SMEM_BYTES = OFF_BAR + (2 * NST + 3) * 8;

__device__ unsigned long long g_acc[2 * 2 * DM];

struct Params {
    const __nv_bfloat16 *kc, *x;
    unsigned long long* acc;
    __nv_bfloat16* out;
    const __nv_bfloat16 *w2, *b1, *b2;
};
struct Maps {
    alignas(64) CUtensorMap wq, v, wo, w1;
};

__device__ __forceinline__ void mbar_init(uint32_t bar, uint32_t cnt) {
    asm volatile("mbarrier.init.shared::cta.b64 [%0], %1;" ::"r"(bar), "r"(cnt) : "memory");
}
__device__ __forceinline__ void mbar_init_fence() { asm volatile("fence.mbarrier_init.release.cluster;" ::: "memory"); }
__device__ __forceinline__ void mbar_expect_tx(uint32_t bar, uint32_t bytes) {
    asm volatile("mbarrier.arrive.expect_tx.shared::cta.b64 _, [%0], %1;" ::"r"(bar), "r"(bytes) : "memory");
}
template <int N>
__device__ __forceinline__ void mbar_arrive(uint32_t bar) {
    asm volatile("mbarrier.arrive.shared::cta.b64 _, [%0], %1;" ::"r"(bar), "n"(N) : "memory");
}
__device__ __forceinline__ void mbar_wait_bounded(uint32_t bar, uint32_t parity) {
    uint32_t ok, n = 0;
    do {
        if (++n > (1u << 18)) __trap();
        asm volatile(
            "{\n.reg .pred p;\nmbarrier.try_wait.parity.shared::cta.b64 p, [%1], %2;\nselp.u32 %0, 1, 0, p;\n}\n"
            : "=r"(ok) : "r"(bar), "r"(parity) : "memory");
    } while (!ok);
}
__device__ __forceinline__ void mbar_wait(uint32_t bar, uint32_t parity) {
    asm volatile(
        "{\n.reg .pred p;\nWAIT_LOOP:\nmbarrier.try_wait.parity.shared::cta.b64 p, [%0], %1;\n@!p bra WAIT_LOOP;\n}\n"
        ::"r"(bar), "r"(parity) : "memory");
}
__device__ __forceinline__ void mbar_wait_cluster(uint32_t bar, uint32_t parity) {
    asm volatile(
        "{\n.reg .pred p;\nWAIT_LOOP:\nmbarrier.try_wait.parity.acquire.cluster.shared::cta.b64 p, [%0], %1;\n@!p bra WAIT_LOOP;\n}\n"
        ::"r"(bar), "r"(parity) : "memory");
}
__device__ __forceinline__ uint64_t policy_evict_first() {
    uint64_t pol;
    asm volatile("createpolicy.fractional.L2::evict_first.b64 %0, 1.0;" : "=l"(pol));
    return pol;
}
__device__ __forceinline__ void bulk_load(uint32_t dst, const void* src, uint32_t bytes, uint32_t bar, uint64_t pol) {
    asm volatile("cp.async.bulk.shared::cluster.global.mbarrier::complete_tx::bytes.L2::cache_hint [%0], [%1], %2, [%3], %4;"
                 ::"r"(dst), "l"(src), "r"(bytes), "r"(bar), "l"(pol) : "memory");
}
__device__ __forceinline__ void tensor_load(uint32_t dst, const CUtensorMap* map, int cx, int cy, uint32_t bar) {
    asm volatile("cp.async.bulk.tensor.2d.shared::cluster.global.mbarrier::complete_tx::bytes [%0], [%1, {%2, %3}], [%4];"
                 ::"r"(dst), "l"(map), "r"(cx), "r"(cy), "r"(bar) : "memory");
}
__device__ __forceinline__ void tensor_load(uint32_t dst, const CUtensorMap* map, int cx, int cy, uint32_t bar, uint64_t pol) {
    asm volatile("cp.async.bulk.tensor.2d.shared::cluster.global.mbarrier::complete_tx::bytes.L2::cache_hint [%0], [%1, {%2, %3}], [%4], %5;"
                 ::"r"(dst), "l"(map), "r"(cx), "r"(cy), "r"(bar), "l"(pol) : "memory");
}
__device__ __forceinline__ void prefetch_map(const CUtensorMap* map) {
    asm volatile("prefetch.tensormap [%0];" ::"l"(map) : "memory");
}
__device__ __forceinline__ uint4 ldg_v4(const void* p) {
    uint4 v;
    asm volatile("ld.global.v4.u32 {%0,%1,%2,%3}, [%4];" : "=r"(v.x), "=r"(v.y), "=r"(v.z), "=r"(v.w) : "l"(p) : "memory");
    return v;
}
__device__ __forceinline__ uint32_t ldg_u16(const void* p) {
    uint16_t v;
    asm volatile("ld.global.u16 %0, [%1];" : "=h"(v) : "l"(p) : "memory");
    return v;
}
__device__ __forceinline__ void ldsm4(uint32_t (&r)[4], uint32_t addr) {
    asm volatile("ldmatrix.sync.aligned.m8n8.x4.shared.b16 {%0,%1,%2,%3}, [%4];"
                 : "=r"(r[0]), "=r"(r[1]), "=r"(r[2]), "=r"(r[3]) : "r"(addr) : "memory");
}
__device__ __forceinline__ void ldsm4t(uint32_t (&r)[4], uint32_t addr) {
    asm volatile("ldmatrix.sync.aligned.m8n8.x4.trans.shared.b16 {%0,%1,%2,%3}, [%4];"
                 : "=r"(r[0]), "=r"(r[1]), "=r"(r[2]), "=r"(r[3]) : "r"(addr) : "memory");
}
__device__ __forceinline__ void mma16816(float (&d)[4], const uint32_t (&a)[4], uint32_t b0, uint32_t b1) {
    asm volatile(
        "mma.sync.aligned.m16n8k16.row.col.f32.bf16.bf16.f32 {%0,%1,%2,%3}, {%4,%5,%6,%7}, {%8,%9}, {%0,%1,%2,%3};"
        : "+f"(d[0]), "+f"(d[1]), "+f"(d[2]), "+f"(d[3])
        : "r"(a[0]), "r"(a[1]), "r"(a[2]), "r"(a[3]), "r"(b0), "r"(b1));
}
__device__ __forceinline__ uint32_t mapa(uint32_t addr, uint32_t rank) {
    uint32_t r;
    asm("mapa.shared::cluster.u32 %0, %1, %2;" : "=r"(r) : "r"(addr), "r"(rank));
    return r;
}
__device__ __forceinline__ void st_async_v4(uint32_t addr, float a, float b, float c, float d, uint32_t bar) {
    asm volatile("st.async.shared::cluster.mbarrier::complete_tx::bytes.v4.f32 [%0], {%1,%2,%3,%4}, [%5];"
                 ::"r"(addr), "f"(a), "f"(b), "f"(c), "f"(d), "r"(bar) : "memory");
}
__device__ __forceinline__ void st_async_v2(uint32_t addr, float a, float b, uint32_t bar) {
    asm volatile("st.async.shared::cluster.mbarrier::complete_tx::bytes.v2.f32 [%0], {%1,%2}, [%3];"
                 ::"r"(addr), "f"(a), "f"(b), "r"(bar) : "memory");
}
__device__ __forceinline__ uint32_t lds_u16(uint32_t addr) {
    uint16_t v;
    asm volatile("ld.shared.u16 %0, [%1];" : "=h"(v) : "r"(addr) : "memory");
    return v;
}
__device__ __forceinline__ uint32_t lds_u32(uint32_t addr) {
    uint32_t v;
    asm volatile("ld.shared.u32 %0, [%1];" : "=r"(v) : "r"(addr) : "memory");
    return v;
}
__device__ __forceinline__ float2 lds_f32x2(uint32_t addr) {
    float2 v;
    asm volatile("ld.shared.v2.f32 {%0,%1}, [%2];" : "=f"(v.x), "=f"(v.y) : "r"(addr) : "memory");
    return v;
}
__device__ __forceinline__ float4 lds_f32x4(uint32_t addr) {
    float4 v;
    asm volatile("ld.shared.v4.f32 {%0,%1,%2,%3}, [%4];" : "=f"(v.x), "=f"(v.y), "=f"(v.z), "=f"(v.w) : "r"(addr) : "memory");
    return v;
}
__device__ __forceinline__ uint4 lds_v4(uint32_t addr) {
    uint4 v;
    asm volatile("ld.shared.v4.u32 {%0,%1,%2,%3}, [%4];" : "=r"(v.x), "=r"(v.y), "=r"(v.z), "=r"(v.w) : "r"(addr) : "memory");
    return v;
}
__device__ __forceinline__ void sts_u16(uint32_t addr, uint32_t v) {
    asm volatile("st.shared.u16 [%0], %1;" ::"r"(addr), "h"((uint16_t)v) : "memory");
}
__device__ __forceinline__ void sts_u32(uint32_t addr, uint32_t v) {
    asm volatile("st.shared.u32 [%0], %1;" ::"r"(addr), "r"(v) : "memory");
}
__device__ __forceinline__ void bar_sync(int id, int n) { asm volatile("bar.sync %0, %1;" ::"r"(id), "r"(n) : "memory"); }
__device__ __forceinline__ void cluster_arrive() { asm volatile("barrier.cluster.arrive.relaxed.aligned;" ::: "memory"); }
__device__ __forceinline__ void cluster_wait() { asm volatile("barrier.cluster.wait.acquire.aligned;" ::: "memory"); }

__device__ __forceinline__ uint32_t pin(uint32_t v) { return __shfl_sync(0xffffffffu, v, threadIdx.x & 31); }
template <class T>
__device__ __forceinline__ T* pin(T* q) {
    const uint64_t v = (uint64_t)q;
    return (T*)(((uint64_t)pin((uint32_t)(v >> 32)) << 32) | pin((uint32_t)v));
}

__device__ __forceinline__ uint32_t pack_bf16(float lo, float hi) {
    uint32_t r;
    asm("cvt.rn.bf16x2.f32 %0, %1, %2;" : "=r"(r) : "f"(hi), "f"(lo));
    return r;
}
__device__ __forceinline__ float bf_lo(uint32_t v) { return __uint_as_float(v << 16); }
__device__ __forceinline__ float bf_hi(uint32_t v) { return __uint_as_float(v & 0xffff0000u); }
__device__ __forceinline__ float rbf(float x) { return bf_lo(pack_bf16(x, 0.f)); }
__device__ __forceinline__ float exp_diff(float a, float b) {
    float r;
    asm("ex2.approx.ftz.f32 %0, %1;" : "=f"(r) : "f"((a - b) * 1.4426950408889634f));
    return r;
}
__device__ __forceinline__ float warp_max(float x) {
    int k = __float_as_int(x);
    k ^= (k >> 31) & 0x7fffffff;
    k = __reduce_max_sync(0xffffffffu, k);
    k ^= (k >> 31) & 0x7fffffff;
    return __int_as_float(k);
}
__device__ __forceinline__ float warp_sum(float x) {
#pragma unroll
    for (int o = 16; o > 0; o >>= 1) x += __shfl_xor_sync(0xffffffffu, x, o);
    return x;
}
__device__ __forceinline__ void unpack8(const uint4& v, float* f) {
    f[0] = bf_lo(v.x); f[1] = bf_hi(v.x); f[2] = bf_lo(v.y); f[3] = bf_hi(v.y);
    f[4] = bf_lo(v.z); f[5] = bf_hi(v.z); f[6] = bf_lo(v.w); f[7] = bf_hi(v.w);
}
__device__ __forceinline__ void ln_stats(const uint4& a, const uint4& b, float& mean_bf, float& sd_bf) {
    float f[16];
    unpack8(a, f); unpack8(b, f + 8);
    float s = 0.f;
#pragma unroll
    for (int i = 0; i < 16; i++) s += f[i];
    const float mean = warp_sum(s) * (1.f / DM);
    float q = 0.f;
#pragma unroll
    for (int i = 0; i < 16; i++) { const float d = f[i] - mean; q = fmaf(d, d, q); }
    const float var = warp_sum(q) * (1.f / DM);
    mean_bf = rbf(mean);
    sd_bf = rbf(__fsqrt_rn(rbf(rbf(var) + 1e-5f)));
}
__device__ __forceinline__ float ln_apply(float x, float mean_bf, float sd_bf) {
    return rbf(__fdiv_rn(rbf(x - mean_bf), sd_bf));
}
__device__ __forceinline__ float2 fold8(const float* c) {
    float v[8];
#pragma unroll
    for (int i = 0; i < 8; i++) v[i] = c[2 * i] + c[2 * (i ^ 1) + 1];
    const float w0 = v[0] + __shfl_xor_sync(0xffffffffu, v[2], 1);
    const float w1 = v[1] + __shfl_xor_sync(0xffffffffu, v[3], 1);
    const float w4 = v[4] + __shfl_xor_sync(0xffffffffu, v[6], 1);
    const float w5 = v[5] + __shfl_xor_sync(0xffffffffu, v[7], 1);
    return make_float2(w0 + __shfl_xor_sync(0xffffffffu, w4, 2), w1 + __shfl_xor_sync(0xffffffffu, w5, 2));
}

__device__ __forceinline__ bool needs_float_path(float asum) {
    const bool huge = __any_sync(0xffffffffu, !(asum < 0x1p14f)), tiny = __all_sync(0xffffffffu, asum < 0x1p-10f);
    return huge | tiny;
}
__device__ __noinline__ void finish_flagged(unsigned long long* a, __nv_bfloat16* o, float sum) {
    float side;
    asm volatile("fence.acq_rel.gpu;" ::: "memory");
    asm volatile("atom.relaxed.gpu.global.exch.b32 %0, [%1+8192], 0;" : "=f"(side) : "l"(a) : "memory");
    asm volatile("st.global.u16 [%0], %1;" ::"l"(o), "h"((uint16_t)pack_bf16(sum + side, 0.f)) : "memory");
    asm volatile("st.global.u64 [%0], %1;" ::"l"(a), "l"(0ull) : "memory");
}
__device__ __forceinline__ void add_fixed(unsigned long long* a, __nv_bfloat16* o, float ys) {
    const long long v = __float2ll_rn(ys);
    uint32_t lo, hi;
    asm volatile("{\n.reg .b64 t;\nmov.b64 t, {%3, %4};\natom.relaxed.gpu.global.add.u64 t, [%2], t;\nmov.b64 {%0, %1}, t;\n}"
                 : "=r"(lo), "=r"(hi) : "l"(a), "r"((uint32_t)v), "r"((uint32_t)(v >> 32) + 0x1000000u) : "memory");
    const unsigned long long r = (((unsigned long long)hi << 32) | lo) + (unsigned long long)(v + (1ll << 31) - ((long long)(NPROD - 1) << 56));
    const uint32_t t = (uint32_t)(r >> 32) + 0x800000u;
    const float frac = (float)(int)((uint32_t)r ^ 0x80000000u);
    const uint32_t pk = pack_bf16(fmaf(frac, 0x1p-32f, (float)(int)(r >> 32)), 0.f);
    asm volatile("{\n.reg .pred p;\nsetp.lt.u32 p, %3, 0x1000000;\n@p st.global.u16 [%0], %1;\n@p st.global.u64 [%2], 0;\n}"
                 ::"l"(o), "h"((uint16_t)pk), "l"(a), "r"(t) : "memory");
    if (__builtin_expect((t ^ 0x80000000u) < 0x1000000u, 0))
        finish_flagged(a, o, fmaf(frac, 0x1p-32f, (float)(int)((uint32_t)(r >> 32) ^ 0x80000000u)));
}
__device__ __noinline__ void add_float(unsigned long long* a, __nv_bfloat16* o, float y) {
    asm volatile("red.relaxed.gpu.global.add.f32 [%0+8192], %1;" ::"l"(a), "f"(y) : "memory");
    asm volatile("red.release.gpu.global.or.b64 [%0], %1;" ::"l"(a), "l"(1ull << 63) : "memory");
    add_fixed(a, o, 0.f);
}
__device__ __forceinline__ void contribute(unsigned long long* a, __nv_bfloat16* o, float y0, float y1, bool float_path) {
    if (__builtin_expect(!float_path, 1)) add_fixed(a, o, fmaf(y1, 0x1p32f, y0 * 0x1p32f));
    else add_float(a, o, y0 + y1);
}

__global__ void __cluster_dims__(2, 1, 1) __launch_bounds__(NTHREADS, 1)
fused_decode_kernel(const __grid_constant__ Params p, const __grid_constant__ Maps maps) {
    extern __shared__ __align__(1024) unsigned char smem[];
    if (threadIdx.x == 0 && blockIdx.x < NATT) {
        const uint32_t ct = blockIdx.x;
        const char* k0 = (const char*)p.kc + (size_t)((((ct >> 1) & 1) * NH + (ct >> 2)) * SK + (SK - WIN) + (ct & 1) * 64) * (DH * 2);
        asm volatile("cp.async.bulk.prefetch.L2.global.L2::cache_hint [%0], %1, %2;"
                     ::"l"(k0), "r"(STAGE), "l"(policy_evict_first()) : "memory");
    }
    const uint32_t sb = (uint32_t)__cvta_generic_to_shared(smem);
    const uint32_t full0 = sb + OFF_BAR, empty0 = full0 + NST * 8;
    const uint32_t qbar = empty0 + NST * 8, obar = qbar + 8, mlbar = obar + 8;
    const int tid = threadIdx.x, warp = tid >> 5, lane = tid & 31;
    const int cta = blockIdx.x;
    const int g = lane >> 2, c = lane & 3;
    const int r = lane & 7, mi = lane >> 3;
    const bool diag = (c == (g >> 1));

    if (cta < NATT) {
        const int rank = cta & 1, b = (cta >> 1) & 1, h = cta >> 2;
        if (warp == 8) {
            const int row0 = (b * NH + h) * SK + (SK - WIN) + rank * 64;
            const char* kp = (const char*)(p.kc + (size_t)row0 * DH);
            const uint64_t pol = policy_evict_first();
            if (lane == 0) {
#pragma unroll
                for (int s = 0; s < NST; s++) mbar_init(full0 + 8 * s, 1);
                mbar_init_fence();
#pragma unroll
                for (int j = 0; j < PRE; j++) {
                    mbar_expect_tx(full0 + 8 * (4 + j), STAGE);
                    bulk_load(sb + (4 + j) * STAGE, kp + j * (2 * STAGE), STAGE, full0 + 8 * (4 + j), pol);
                }
#pragma unroll
                for (int s = 0; s < 4; s++) {
                    mbar_expect_tx(full0 + 8 * s, STAGE);
                    tensor_load(sb + s * STAGE, &maps.wq, h * DH, rank * 256 + s * 64, full0 + 8 * s);
                }
#pragma unroll
                for (int j = PRE; j < NST - 4; j++) {
                    mbar_expect_tx(full0 + 8 * (4 + j), STAGE);
                    bulk_load(sb + (4 + j) * STAGE, kp + j * (2 * STAGE), STAGE, full0 + 8 * (4 + j), pol);
                }
#pragma unroll
                for (int s = 0; s < NST; s++) mbar_init(empty0 + 8 * s, 8);
#pragma unroll
                for (int s = 0; s < 3; s++) mbar_init(qbar + 8 * s, 1);
                mbar_init_fence();
                mbar_expect_tx(qbar, 16 * 512);
                mbar_expect_tx(obar, 1024);
                mbar_expect_tx(mlbar, 16 * 8);
                prefetch_map(&maps.wo);
                prefetch_map(&maps.v);
            }
            __syncwarp();
            cluster_arrive();
            cluster_wait();
            if (lane == 0) {
                int s = 0, ph = 0;
#pragma unroll 1
                for (int i = NST; i < 72; i++) {
                    mbar_wait_bounded(empty0 + 8 * s, ph);
                    mbar_expect_tx(full0 + 8 * s, STAGE);
                    if (i < 36) bulk_load(sb + s * STAGE, kp + (i - 4) * (2 * STAGE), STAGE, full0 + 8 * s, pol);
                    else if (i < 40) tensor_load(sb + s * STAGE, &maps.wo, rank * 256 + (i - 36) * 64, h * DH, full0 + 8 * s);
                    else tensor_load(sb + s * STAGE, &maps.v, 0, 2 * row0 + (i - 40) * 256, full0 + 8 * s, pol);
                    if (++s == NST) { s = 0; ph ^= 1; }
                }
                mbar_wait_bounded(obar, 0);
            }
        } else {
            const int grp = warp >> 2, w4 = warp & 3;
            const bool e = g & 1;
            uint32_t qf[8][2];
            {
                const __nv_bfloat16* xb = p.x + b * DM;
                const uint4 xs0 = ldg_v4(xb + lane * 16), xs1 = ldg_v4(xb + lane * 16 + 8);
                uint32_t xr[4];
#pragma unroll
                for (int i = 0; i < 4; i++) xr[i] = ldg_u16(xb + rank * 256 + (grp + (i & 2)) * 64 + w4 * 16 + (i & 1) * 8 + g);
                cluster_arrive();
                float mean_bf, sd_bf;
                ln_stats(xs0, xs1, mean_bf, sd_bf);
#pragma unroll
                for (int i = 0; i < 4; i++)
                    xr[i] = diag ? __float_as_uint(ln_apply(bf_lo(xr[i]), mean_bf, sd_bf)) >> (e ? 0 : 16) : 0u;
                float o[8][4];
#pragma unroll
                for (int j = 0; j < 8; j++) { o[j][0] = o[j][1] = o[j][2] = o[j][3] = 0.f; }
                cluster_wait();
#pragma unroll
                for (int t = 0; t < 2; t++) {
                    const int s = grp + 2 * t;
                    const uint32_t wb = sb + s * STAGE + (w4 * 16 + r + 8 * (mi >> 1)) * 256 + (mi & 1) * 128 + r * 16;
                    mbar_wait(full0 + 8 * s, 0);
                    uint32_t a[8][4];
#pragma unroll
                    for (int j = 0; j < 8; j++) ldsm4t(a[j], wb ^ (j << 4));
#pragma unroll
                    for (int j = 0; j < 8; j++) mma16816(o[j], a[j], xr[2 * t], xr[2 * t + 1]);
                    __syncwarp();
                    if (lane == 0) mbar_arrive<2>(empty0 + 8 * s);
                }
                float lo[16], hi[16];
#pragma unroll
                for (int j = 0; j < 8; j++) { lo[2 * j] = o[j][0]; lo[2 * j + 1] = o[j][1]; hi[2 * j] = o[j][2]; hi[2 * j + 1] = o[j][3]; }
                const float2 u0 = fold8(lo), u1 = fold8(hi);
                const uint32_t slot = sb + OFF_QPART + (rank * 8 + warp) * 512 + lane * 16;
                st_async_v4(mapa(slot, 0), u0.x, u0.y, u1.x, u1.y, mapa(qbar, 0));
                st_async_v4(mapa(slot, 1), u0.x, u0.y, u1.x, u1.y, mapa(qbar, 1));
                if (tid < 128) {
                    mbar_wait_cluster(qbar, 0);
                    float sum = 0.f;
#pragma unroll
                    for (int i = 0; i < 16; i++) sum += __uint_as_float(lds_u32(sb + OFF_QPART + i * 512 + tid * 4));
                    const int col = (tid & 2) * 32 + ((tid >> 2) & 3) * 16 + (tid & 1) * 8 + (tid >> 4);
                    sts_u16(sb + OFF_QBF + col * 2, pack_bf16(sum, 0.f));
                }
                bar_sync(1, 256);
#pragma unroll
                for (int j = 0; j < 8; j++) {
                    qf[j][0] = lds_u32(sb + OFF_QBF + ((j ^ g) * 16) + c * 4);
                    qf[j][1] = lds_u32(sb + OFF_QBF + 128 + ((j ^ g) * 16) + c * 4);
                }
            }
            {
                const uint32_t koff = (w4 * 16 + r + 8 * (mi & 1)) * 256 + (mi >> 1) * 128 + r * 16;
                uint32_t sdst = sb + OFF_S + (grp * 64 + w4 * 16 + g) * 2;
                int s = 4 + grp, ph = 0;
#pragma unroll 1
                for (int it = 0; it < 16; it++) {
                    const uint32_t kb = sb + s * STAGE + koff;
                    mbar_wait(full0 + 8 * s, ph);
                    float sa[4] = {0.f, 0.f, 0.f, 0.f}, sc[4] = {0.f, 0.f, 0.f, 0.f};
                    uint32_t a[8][4];
#pragma unroll
                    for (int j = 0; j < 8; j++) ldsm4(a[j], kb ^ (j << 4));
#pragma unroll
                    for (int j = 0; j < 8; j += 2) {
                        mma16816(sa, a[j], qf[j][0], qf[j][1]);
                        mma16816(sc, a[j + 1], qf[j + 1][0], qf[j + 1][1]);
                    }
                    __syncwarp();
                    if (lane == 0) mbar_arrive<2>(empty0 + 8 * s);
                    uint32_t pk = pack_bf16(e ? sa[1] + sc[1] : sa[0] + sc[0], e ? sa[3] + sc[3] : sa[2] + sc[2]);
                    pk = pack_bf16(bf_lo(pk) * 0.08838834764831845f, bf_hi(pk) * 0.08838834764831845f);
                    if (diag) { sts_u16(sdst, pk); sts_u16(sdst + 16, pk >> 16); }
                    sdst += 256;
                    s += 2;
                    if (s >= NST) { s -= NST; ph ^= 1; }
                }
            }
            {
                __syncwarp();
                const int t = (lane & 30) + grp, hf = lane & 1;
                float sv[8];
                unpack8(lds_v4(sb + OFF_S + (t * 64 + w4 * 16 + hf * 8) * 2), sv);
                float m = -3.4028234663852886e38f;
#pragma unroll
                for (int i = 0; i < 8; i++) m = fmaxf(m, sv[i]);
                m = warp_max(m);
                float l = 0.f;
#pragma unroll
                for (int i = 0; i < 8; i++) { sv[i] = exp_diff(sv[i], m); l += sv[i]; }
                l = warp_sum(l);
                if (lane < 2) st_async_v2(mapa(sb + OFF_ML + (rank * 8 + warp) * 8, lane), m, l, mapa(mlbar, lane));
                mbar_wait_cluster(mlbar, 0);
                const float2 ml = lds_f32x2(sb + OFF_ML + (lane & 15) * 8);
                const float M = warp_max(ml.x);
                float L = exp_diff(ml.x, M) * ml.y;
#pragma unroll
                for (int ofs = 8; ofs > 0; ofs >>= 1) L += __shfl_xor_sync(0xffffffffu, L, ofs);
                const float f = __fdiv_rn(exp_diff(m, M), L);
#pragma unroll
                for (int j = 0; j < 4; j++) sts_u32(sb + OFF_P + t * 128 + j * 32 + w4 * 8 + hf * 4, pack_bf16(sv[2 * j] * f, sv[2 * j + 1] * f));
            }
            uint32_t wa[8][2][4];
            {
                const int t4 = 36 + (warp >> 1), st = t4 % NST;
                mbar_wait(full0 + 8 * st, (t4 / NST) & 1);
                const uint32_t wb = sb + st * STAGE + (r + 8 * (mi >> 1)) * 128 + ((4 * (warp & 1) + (mi & 1)) ^ r) * 16;
#pragma unroll
                for (int t = 0; t < 8; t++)
#pragma unroll
                    for (int j = 0; j < 2; j++) ldsm4t(wa[t][j], (wb ^ (((2 * j) ^ (t >> 1)) << 4)) + t * 2048);
                __syncwarp();
                if (lane == 0) mbar_arrive<4>(empty0 + 8 * st);
            }
            const uint32_t vbase = pin(sb + (8 * (mi >> 1) + r) * 256 + grp * 128 + ((2 * w4) ^ (mi & 1) ^ (r >> 2) ^ (2 * (r & 3) + grp)) * 16);
            const uint32_t o_dst = pin(mapa(sb + OFF_OPART + rank * 512 + (warp * 8 + g) * 8, c & 1)), o_bar = pin(mapa(obar, c & 1));
            const uint32_t o_src = pin(sb + OFF_OPART + lane * 16), obar_p = pin(obar);
            uint32_t omask[8];
#pragma unroll
            for (int t = 0; t < 8; t++) omask[t] = pin(g == t ? 0xffffffffu : 0u);
            unsigned long long* const acc_p = pin(p.acc + b * DM + rank * 256 + tid);
            __nv_bfloat16* const out_p = pin(p.out + b * DM + rank * 256 + warp * 32 + c * 8 + g);
            const bool feed = pin((uint32_t)((c >> 1) == (g & 1))), send = pin((uint32_t)(c < 2));
            bar_sync(1, 256);
            float oc[4][4];
#pragma unroll
            for (int j = 0; j < 4; j++) { oc[j][0] = oc[j][1] = oc[j][2] = oc[j][3] = 0.f; }
            {
                auto pv_tile = [&](uint32_t vb, const uint4& p0, const uint4& p1) {
                    uint32_t a[4][4];
#pragma unroll
                    for (int j = 0; j < 4; j++) ldsm4t(a[j], vb + j * 4096);
                    mma16816(oc[0], a[0], p0.x, p0.y);
                    mma16816(oc[1], a[1], p0.z, p0.w);
                    mma16816(oc[2], a[2], p1.x, p1.y);
                    mma16816(oc[3], a[3], p1.z, p1.w);
                };
                uint32_t psrc = sb + OFF_P + c * 32;
                uint4 pe[EG][2];
#pragma unroll
                for (int j = 0; j < EG; j++) {
                    pe[j][0] = pe[j][1] = make_uint4(0u, 0u, 0u, 0u);
                    if (feed) { pe[j][0] = lds_v4(psrc + (32 - EG + j) * 128); pe[j][1] = lds_v4(psrc + (32 - EG + j) * 128 + 16); }
                }
                int s = 40 % NST, ph = (40 / NST) & 1;
#pragma unroll 1
                for (int it = 0; it < 32 - EG; it++) {
                    uint4 p0 = make_uint4(0u, 0u, 0u, 0u), p1 = p0;
                    if (feed) { p0 = lds_v4(psrc); p1 = lds_v4(psrc + 16); }
                    psrc += 128;
                    mbar_wait(full0 + 8 * s, ph);
                    pv_tile(vbase + s * STAGE, p0, p1);
                    __syncwarp();
                    if (lane == 0) mbar_arrive<1>(empty0 + 8 * s);
                    if (++s == NST) { s = 0; ph ^= 1; }
                }
#pragma unroll
                for (int j = 0; j < EG; j++) {
                    mbar_wait(full0 + 8 * (NST - EG + j), (72 / NST - 1) & 1);
                    pv_tile(vbase + (NST - EG + j) * STAGE, pe[j][0], pe[j][1]);
                }
            }
            const float oa0 = (((oc[0][0] + oc[0][3]) + (oc[1][0] + oc[1][3])) + (oc[2][0] + oc[2][3])) + (oc[3][0] + oc[3][3]);
            const float oa1 = (((oc[0][1] + oc[0][2]) + (oc[1][1] + oc[1][2])) + (oc[2][1] + oc[2][2])) + (oc[3][1] + oc[3][2]);
            if (send) st_async_v2(o_dst, oa0, oa1, o_bar);
            mbar_wait(obar_p, 0);
            const float4 u = lds_f32x4(o_src), v = lds_f32x4(o_src + 512);
            const uint32_t f0 = pack_bf16(u.x + v.x, u.z + v.z), f1 = pack_bf16(u.y + v.y, u.w + v.w);
            float y[2][2][4];
#pragma unroll
            for (int j = 0; j < 4; j++) { y[j >> 1][j & 1][0] = y[j >> 1][j & 1][1] = y[j >> 1][j & 1][2] = y[j >> 1][j & 1][3] = 0.f; }
#pragma unroll
            for (int t = 0; t < 8; t++) {
                mma16816(y[t & 1][1], wa[t][1], f0 & omask[t], f1 & omask[t]);
                mma16816(y[t & 1][0], wa[t][0], f0 & omask[t], f1 & omask[t]);
            }
            const float v3 = y[0][1][2] + y[1][1][3], v2 = y[0][1][0] + y[1][1][1];
            const float v1 = y[0][0][2] + y[1][0][3], v0 = y[0][0][0] + y[1][0][1];
            const float w2 = v2 + __shfl_xor_sync(0xffffffffu, v3, 1);
            const float w0 = v0 + __shfl_xor_sync(0xffffffffu, v1, 1);
            const float x2 = __shfl_xor_sync(0xffffffffu, w2, 2);
            contribute(acc_p, out_p, w0, x2, needs_float_path((fabsf(v0) + fabsf(v1)) + (fabsf(v2) + fabsf(v3))));
        }
    } else {
        const int fj = cta - NATT;
        const int sh1 = fj & 1;
        const int T1 = 32 + sh1, T2 = (fj == NFFN - 1) ? (FF - (NFFN - 1) * FSL) / 16 : FSL / 16;
        if (warp == 8) {
            if (lane == 0) {
                prefetch_map(&maps.w1);
#pragma unroll
                for (int s = 0; s < NST; s++) { mbar_init(full0 + 8 * s, 1); mbar_init(empty0 + 8 * s, 8); }
                mbar_init_fence();
            }
            __syncwarp();
            bar_sync(3, NTHREADS);
            if (lane == 0) {
                const char* p2 = (const char*)(p.w2 + (size_t)fj * FSL * DM);
                const uint64_t pol = policy_evict_first();
                int s = 0, ph = 1;
#pragma unroll 1
                for (int i = 0; i < T1 + T2 + NST; i++) {
                    mbar_wait_bounded(empty0 + 8 * s, ph);
                    if (i < T1) {
                        mbar_expect_tx(full0 + 8 * s, 16 * FSL * 2);
                        tensor_load(sb + s * STAGE, &maps.w1, fj * (FSL / 2), i * 16 - sh1, full0 + 8 * s, pol);
                    } else if (i < T1 + T2) {
                        mbar_expect_tx(full0 + 8 * s, STAGE);
                        bulk_load(sb + s * STAGE, p2 + (size_t)(i - T1) * STAGE, STAGE, full0 + 8 * s, pol);
                    }
                    if (++s == NST) { s = 0; ph ^= 1; }
                }
            }
        } else {
            const uint32_t xn_s = sb + OFF_QPART;
            const uint32_t g_s = xn_s + 2 * 1056;
            const uint4 xs0 = ldg_v4(p.x + (warp & 1) * DM + lane * 16), xs1 = ldg_v4(p.x + (warp & 1) * DM + lane * 16 + 8);
            uint32_t bias_raw[6], res_raw[6];
#pragma unroll
            for (int j = 0; j < 6; j++) bias_raw[j] = ldg_u16(p.b1 + min(fj * FSL + (warp + 8 * (j >> 1)) * 16 + (j & 1) * 8 + g, FF - 1));
#pragma unroll
            for (int j = 0; j < 6; j++) res_raw[j] = ldg_u16((j < 4 ? p.x + (j >> 1) * DM : p.b2) + warp * 64 + c * 16 + (j & 1) * 8 + g);
            bar_sync(3, NTHREADS);
            if (warp < 2) {
                float mean_bf, sd_bf, xn[16];
                ln_stats(xs0, xs1, mean_bf, sd_bf);
                unpack8(xs0, xn); unpack8(xs1, xn + 8);
#pragma unroll
                for (int i = 0; i < 16; i++) sts_u16(xn_s + warp * 1056 + (lane * 16 + i + sh1) * 2, pack_bf16(ln_apply(xn[i], mean_bf, sd_bf), 0.f));
                if (lane < 16) sts_u16(xn_s + warp * 1056 + (lane == 15 && sh1 ? 0 : DM + sh1 + lane) * 2, 0);
            }
            bar_sync(1, 256);
            int s = 0, ph = 0;
            float hacc[3][4];
#pragma unroll
            for (int j = 0; j < 3; j++) { hacc[j][0] = hacc[j][1] = hacc[j][2] = hacc[j][3] = 0.f; }
            uint32_t aoff[3];
#pragma unroll
            for (int j = 0; j < 3; j++) aoff[j] = (r + 8 * (mi >> 1)) * (FSL * 2) + min(2 * (warp + 8 * j) + (mi & 1), FSL / 8 - 1) * 16;
#pragma unroll 1
            for (int i = 0; i < T1; i++) {
                uint32_t f0 = 0, f1 = 0;
                if (g < 2) { f0 = lds_u32(xn_s + g * 1056 + i * 32 + c * 4); f1 = lds_u32(xn_s + g * 1056 + i * 32 + 16 + c * 4); }
                mbar_wait(full0 + 8 * s, ph);
#pragma unroll
                for (int j = 0; j < 3; j++) {
                    uint32_t a[4];
                    ldsm4t(a, sb + s * STAGE + aoff[j]);
                    mma16816(hacc[j], a, f0, f1);
                }
                __syncwarp();
                if (lane == 0) mbar_arrive<1>(empty0 + 8 * s);
                if (++s == NST) { s = 0; ph ^= 1; }
            }
            if (c == 0) {
#pragma unroll
                for (int j = 0; j < 3; j++)
#pragma unroll
                    for (int hf = 0; hf < 2; hf++) {
                        const int f = (warp + 8 * j) * 16 + hf * 8 + g;
                        if (f < FSL) {
                            const float bias = bf_lo(bias_raw[2 * j + hf]);
#pragma unroll
                            for (int bb = 0; bb < 2; bb++) {
                                const float hv = rbf(rbf(hacc[j][2 * hf + bb]) + bias);
                                const float inner = 0.7978845608028654f * (hv + 0.044715f * hv * hv * hv);
                                sts_u16(g_s + bb * 704 + f * 2, pack_bf16(0.5f * hv * (1.f + tanhf(inner)), 0.f));
                            }
                        }
                    }
            }
            bar_sync(1, 256);
            float y[2][4][4];
#pragma unroll
            for (int bb = 0; bb < 2; bb++)
#pragma unroll
                for (int j = 0; j < 4; j++) { y[bb][j][0] = y[bb][j][1] = y[bb][j][2] = y[bb][j][3] = 0.f; }
            const int sh = (g & 1) * 16;
#pragma unroll 1
            for (int i = 0; i < T2; i++) {
                uint32_t f[2][2] = {{0u, 0u}, {0u, 0u}};
                if (diag) {
#pragma unroll
                    for (int bb = 0; bb < 2; bb++) {
                        f[bb][0] = lds_u16(g_s + bb * 704 + (i * 16 + g) * 2) << sh;
                        f[bb][1] = lds_u16(g_s + bb * 704 + (i * 16 + 8 + g) * 2) << sh;
                    }
                }
                const uint32_t wb = sb + s * STAGE + (r + 8 * (mi >> 1)) * 1024 + warp * 128 + (((mi & 1) * 4) ^ r) * 16;
                mbar_wait(full0 + 8 * s, ph);
#pragma unroll
                for (int j = 0; j < 4; j++) {
                    uint32_t a[4];
                    ldsm4t(a, wb ^ (j << 4));
                    mma16816(y[0][j], a, f[0][0], f[0][1]);
                    mma16816(y[1][j], a, f[1][0], f[1][1]);
                }
                __syncwarp();
                if (lane == 0) mbar_arrive<1>(empty0 + 8 * s);
                if (++s == NST) { s = 0; ph ^= 1; }
            }
#pragma unroll
            for (int bb = 0; bb < 2; bb++) {
                float yy[16];
#pragma unroll
                for (int j = 0; j < 4; j++) { yy[2 * j] = y[bb][j][0]; yy[2 * j + 1] = y[bb][j][1]; yy[8 + 2 * j] = y[bb][j][2]; yy[8 + 2 * j + 1] = y[bb][j][3]; }
                float2 yo = fold8(yy);
                if (fj == 0) {
                    yo.x += bf_lo(res_raw[2 * bb]) + bf_lo(res_raw[4]);
                    yo.y += bf_lo(res_raw[2 * bb + 1]) + bf_lo(res_raw[5]);
                }
                const int n0 = bb * DM + warp * 64 + c * 16;
                unsigned long long* a = p.acc + (n0 & ~31) + 4 * g + 2 * (c & 1);
                const bool fp = needs_float_path(fabsf(yo.x) + fabsf(yo.y));
                contribute(a, p.out + n0 + g, yo.x, 0.f, fp);
                contribute(a + 1, p.out + n0 + 8 + g, yo.y, 0.f, fp);
            }
        }
    }
}

typedef CUresult (*EncodeFn)(CUtensorMap*, CUtensorMapDataType, cuuint32_t, void*, const cuuint64_t*, const cuuint64_t*,
                             const cuuint32_t*, const cuuint32_t*, CUtensorMapInterleave, CUtensorMapSwizzle,
                             CUtensorMapL2promotion, CUtensorMapFloatOOBfill);

void encode_2d(EncodeFn fn, CUtensorMap* map, CUtensorMapDataType dt, const void* base, uint64_t cols, uint64_t rows,
               uint64_t pitch_bytes, uint32_t box_cols, uint32_t box_rows, CUtensorMapSwizzle sw) {
    const cuuint64_t dims[2] = {cols, rows}, strides[1] = {pitch_bytes};
    const cuuint32_t box[2] = {box_cols, box_rows}, estr[2] = {1, 1};
    fn(map, dt, 2, const_cast<void*>(base), dims, strides, box, estr, CU_TENSOR_MAP_INTERLEAVE_NONE, sw,
       CU_TENSOR_MAP_L2_PROMOTION_NONE, CU_TENSOR_MAP_FLOAT_OOB_FILL_NONE);
}

}

extern "C" void kernel_launch(void* const* d_in, const int* in_sizes, int n_in, void* d_out, int out_size) {
    (void)in_sizes; (void)n_in; (void)out_size;
    typedef const __nv_bfloat16* P;
    static EncodeFn encode = nullptr;
    static void* acc = nullptr;
    if (!encode) {
        cudaFuncSetAttribute(fused_decode_kernel, cudaFuncAttributeMaxDynamicSharedMemorySize, SMEM_BYTES);
        cudaDriverEntryPointQueryResult st;
        cudaGetDriverEntryPoint("cuTensorMapEncodeTiled", (void**)&encode, cudaEnableDefault, &st);
        cudaGetSymbolAddress(&acc, g_acc);
    }
    Params p;
    p.kc = (P)d_in[1]; p.x = (P)d_in[0];
    p.acc = (unsigned long long*)acc; p.out = (__nv_bfloat16*)d_out;
    p.w2 = (P)d_in[8]; p.b1 = (P)d_in[7]; p.b2 = (P)d_in[9];
    Maps maps;
    encode_2d(encode, &maps.wq, CU_TENSOR_MAP_DATA_TYPE_BFLOAT16, d_in[3], NH * DH, DM, NH * DH * 2, DH, 64,
              CU_TENSOR_MAP_SWIZZLE_NONE);
    encode_2d(encode, &maps.v, CU_TENSOR_MAP_DATA_TYPE_BFLOAT16, d_in[2], 64, (uint64_t)2 * 2 * NH * SK, 128, 64, 128,
              CU_TENSOR_MAP_SWIZZLE_128B);
    encode_2d(encode, &maps.wo, CU_TENSOR_MAP_DATA_TYPE_BFLOAT16, d_in[4], DM, NH * DH, DM * 2, 64, 128,
              CU_TENSOR_MAP_SWIZZLE_128B);
    encode_2d(encode, &maps.w1, CU_TENSOR_MAP_DATA_TYPE_UINT32, d_in[6], FF / 2, DM, FF * 2, FSL / 2, 16,
              CU_TENSOR_MAP_SWIZZLE_NONE);
    fused_decode_kernel<<<NCTA, NTHREADS, SMEM_BYTES>>>(p, maps);
}
```

```cpp
#include <cuda.h>
#include <cuda_runtime.h>
#include <cuda_bf16.h>
#include <stdint.h>

namespace {

constexpr int DM = 512, NH = 32, SK = 16384, WIN = 4096, DH = 128, FF = 1376;
constexpr int NATT = 128, NFFN = 4, NCTA = NATT + NFFN;
constexpr int NPROD = NH + NFFN;
constexpr int FSL = 352;
constexpr int NST = 8;
constexpr int STAGE = 16384;
constexpr int PRE = 2;
constexpr int EG = 4;
constexpr int NTHREADS = 288;
static_assert(NST % 2 == 0 && 72 % NST == 0 && EG <= NST, "ring geometry");

constexpr int OFF_QPART = NST * STAGE;
constexpr int OFF_S = OFF_QPART, OFF_P = OFF_QPART + 4096;
constexpr int OFF_OPART = OFF_QPART + 8192;
constexpr int OFF_ML = OFF_OPART + 512;
constexpr int OFF_QBF = OFF_ML + 128;
constexpr int OFF_BAR = OFF_QBF + 256;
constexpr int SMEM_BYTES = OFF_BAR + (2 * NST + 3) * 8;

__device__ __align__(256) unsigned long long g_acc[2 * 2 * DM];

struct Params {
    const __nv_bfloat16 *kc, *x;
    unsigned long long* acc;
    __nv_bfloat16* out;
    const __nv_bfloat16 *w2, *b1, *b2;
};
struct Maps {
    alignas(64) CUtensorMap wq, v, wo, w1;
};

__device__ __forceinline__ void mbar_init(uint32_t bar, uint32_t cnt) {
    asm volatile("mbarrier.init.shared::cta.b64 [%0], %1;" ::"r"(bar), "r"(cnt) : "memory");
}
__device__ __forceinline__ void mbar_init_fence() { asm volatile("fence.mbarrier_init.release.cluster;" ::: "memory"); }
__device__ __forceinline__ void mbar_expect_tx(uint32_t bar, uint32_t bytes) {
    asm volatile("mbarrier.arrive.expect_tx.shared::cta.b64 _, [%0], %1;" ::"r"(bar), "r"(bytes) : "memory");
}
template <int N>
__device__ __forceinline__ void mbar_arrive(uint32_t bar) {
    asm volatile("mbarrier.arrive.shared::cta.b64 _, [%0], %1;" ::"r"(bar), "n"(N) : "memory");
}
template <int N>
__device__ __forceinline__ void release_stage(uint32_t bar, int lane) {
    asm volatile("fence.proxy.async.shared::cta;" ::: "memory");
    __syncwarp();
    if (lane == 0) mbar_arrive<N>(bar);
}
#define WAIT_LIMIT (1u << 18)
__device__ __forceinline__ void mbar_wait_bounded(uint32_t bar, uint32_t parity) {
    uint32_t ok, n = 0;
    do {
        if (++n > WAIT_LIMIT) __trap();
        asm volatile(
            "{\n.reg .pred p;\nmbarrier.try_wait.parity.shared::cta.b64 p, [%1], %2;\nselp.u32 %0, 1, 0, p;\n}\n"
            : "=r"(ok) : "r"(bar), "r"(parity) : "memory");
    } while (!ok);
}
__device__ __forceinline__ void mbar_wait(uint32_t bar, uint32_t parity) {
    asm volatile(
        "{\n.reg .pred p;\nWAIT_LOOP:\nmbarrier.try_wait.parity.shared::cta.b64 p, [%0], %1;\n@!p bra WAIT_LOOP;\n}\n"
        ::"r"(bar), "r"(parity) : "memory");
}
__device__ __forceinline__ void mbar_wait_cluster(uint32_t bar, uint32_t parity) {
    asm volatile(
        "{\n.reg .pred p;\nWAIT_LOOP:\nmbarrier.try_wait.parity.acquire.cluster.shared::cta.b64 p, [%0], %1;\n@!p bra WAIT_LOOP;\n}\n"
        ::"r"(bar), "r"(parity) : "memory");
}
__device__ __forceinline__ uint64_t policy_evict_first() {
    uint64_t pol;
    asm volatile("createpolicy.fractional.L2::evict_first.b64 %0, 1.0;" : "=l"(pol));
    return pol;
}
__device__ __forceinline__ void bulk_load(uint32_t dst, const void* src, uint32_t bytes, uint32_t bar, uint64_t pol) {
    asm volatile("cp.async.bulk.shared::cluster.global.mbarrier::complete_tx::bytes.L2::cache_hint [%0], [%1], %2, [%3], %4;"
                 ::"r"(dst), "l"(src), "r"(bytes), "r"(bar), "l"(pol) : "memory");
}
__device__ __forceinline__ void tensor_load(uint32_t dst, const CUtensorMap* map, int cx, int cy, uint32_t bar) {
    asm volatile("cp.async.bulk.tensor.2d.shared::cluster.global.mbarrier::complete_tx::bytes [%0], [%1, {%2, %3}], [%4];"
                 ::"r"(dst), "l"(map), "r"(cx), "r"(cy), "r"(bar) : "memory");
}
__device__ __forceinline__ void tensor_load(uint32_t dst, const CUtensorMap* map, int cx, int cy, uint32_t bar, uint64_t pol) {
    asm volatile("cp.async.bulk.tensor.2d.shared::cluster.global.mbarrier::complete_tx::bytes.L2::cache_hint [%0], [%1, {%2, %3}], [%4], %5;"
                 ::"r"(dst), "l"(map), "r"(cx), "r"(cy), "r"(bar), "l"(pol) : "memory");
}
__device__ __forceinline__ void prefetch_map(const CUtensorMap* map) {
    asm volatile("prefetch.tensormap [%0];" ::"l"(map) : "memory");
}
__device__ __forceinline__ uint4 ldg_v4(const void* p) {
    uint4 v;
    asm volatile("ld.global.v4.u32 {%0,%1,%2,%3}, [%4];" : "=r"(v.x), "=r"(v.y), "=r"(v.z), "=r"(v.w) : "l"(p) : "memory");
    return v;
}
__device__ __forceinline__ uint32_t ldg_u16(const void* p) {
    uint16_t v;
    asm volatile("ld.global.u16 %0, [%1];" : "=h"(v) : "l"(p) : "memory");
    return v;
}
__device__ __forceinline__ void ldsm4(uint32_t (&r)[4], uint32_t addr) {
    asm volatile("ldmatrix.sync.aligned.m8n8.x4.shared.b16 {%0,%1,%2,%3}, [%4];"
                 : "=r"(r[0]), "=r"(r[1]), "=r"(r[2]), "=r"(r[3]) : "r"(addr) : "memory");
}
__device__ __forceinline__ void ldsm4t(uint32_t (&r)[4], uint32_t addr) {
    asm volatile("ldmatrix.sync.aligned.m8n8.x4.trans.shared.b16 {%0,%1,%2,%3}, [%4];"
                 : "=r"(r[0]), "=r"(r[1]), "=r"(r[2]), "=r"(r[3]) : "r"(addr) : "memory");
}
__device__ __forceinline__ void mma16816(float (&d)[4], const uint32_t (&a)[4], uint32_t b0, uint32_t b1) {
    asm volatile(
        "mma.sync.aligned.m16n8k16.row.col.f32.bf16.bf16.f32 {%0,%1,%2,%3}, {%4,%5,%6,%7}, {%8,%9}, {%0,%1,%2,%3};"
        : "+f"(d[0]), "+f"(d[1]), "+f"(d[2]), "+f"(d[3])
        : "r"(a[0]), "r"(a[1]), "r"(a[2]), "r"(a[3]), "r"(b0), "r"(b1));
}
__device__ __forceinline__ uint32_t mapa(uint32_t addr, uint32_t rank) {
    uint32_t r;
    asm("mapa.shared::cluster.u32 %0, %1, %2;" : "=r"(r) : "r"(addr), "r"(rank));
    return r;
}
__device__ __forceinline__ void st_async_v4(uint32_t addr, float a, float b, float c, float d, uint32_t bar) {
    asm volatile("st.async.shared::cluster.mbarrier::complete_tx::bytes.v4.f32 [%0], {%1,%2,%3,%4}, [%5];"
                 ::"r"(addr), "f"(a), "f"(b), "f"(c), "f"(d), "r"(bar) : "memory");
}
__device__ __forceinline__ void st_async_v2(uint32_t addr, float a, float b, uint32_t bar) {
    asm volatile("st.async.shared::cluster.mbarrier::complete_tx::bytes.v2.f32 [%0], {%1,%2}, [%3];"
                 ::"r"(addr), "f"(a), "f"(b), "r"(bar) : "memory");
}
__device__ __forceinline__ uint32_t lds_u16(uint32_t addr) {
    uint16_t v;
    asm volatile("ld.shared.u16 %0, [%1];" : "=h"(v) : "r"(addr) : "memory");
    return v;
}
__device__ __forceinline__ uint32_t lds_u32(uint32_t addr) {
    uint32_t v;
    asm volatile("ld.shared.u32 %0, [%1];" : "=r"(v) : "r"(addr) : "memory");
    return v;
}
__device__ __forceinline__ float2 lds_f32x2(uint32_t addr) {
    float2 v;
    asm volatile("ld.shared.v2.f32 {%0,%1}, [%2];" : "=f"(v.x), "=f"(v.y) : "r"(addr) : "memory");
    return v;
}
__device__ __forceinline__ uint4 lds_v4(uint32_t addr) {
    uint4 v;
    asm volatile("ld.shared.v4.u32 {%0,%1,%2,%3}, [%4];" : "=r"(v.x), "=r"(v.y), "=r"(v.z), "=r"(v.w) : "r"(addr) : "memory");
    return v;
}
__device__ __forceinline__ void sts_u16(uint32_t addr, uint32_t v) {
    asm volatile("st.shared.u16 [%0], %1;" ::"r"(addr), "h"((uint16_t)v) : "memory");
}
__device__ __forceinline__ void sts_u32(uint32_t addr, uint32_t v) {
    asm volatile("st.shared.u32 [%0], %1;" ::"r"(addr), "r"(v) : "memory");
}
__device__ __forceinline__ void bar_sync(int id, int n) { asm volatile("bar.sync %0, %1;" ::"r"(id), "r"(n) : "memory"); }
__device__ __forceinline__ void cluster_arrive() { asm volatile("barrier.cluster.arrive.relaxed.aligned;" ::: "memory"); }
__device__ __forceinline__ void cluster_wait() { asm volatile("barrier.cluster.wait.acquire.aligned;" ::: "memory"); }

__device__ __forceinline__ uint32_t pin(uint32_t v) { return __shfl_sync(0xffffffffu, v, threadIdx.x & 31); }
template <class T>
__device__ __forceinline__ T* pin(T* q) {
    const uint64_t v = (uint64_t)q;
    return (T*)(((uint64_t)pin((uint32_t)(v >> 32)) << 32) | pin((uint32_t)v));
}

__device__ __forceinline__ uint32_t pack_bf16(float lo, float hi) {
    uint32_t r;
    asm("cvt.rn.bf16x2.f32 %0, %1, %2;" : "=r"(r) : "f"(hi), "f"(lo));
    return r;
}
__device__ __forceinline__ float bf_lo(uint32_t v) { return __uint_as_float(v << 16); }
__device__ __forceinline__ float bf_hi(uint32_t v) { return __uint_as_float(v & 0xffff0000u); }
__device__ __forceinline__ float rbf(float x) { return bf_lo(pack_bf16(x, 0.f)); }
__device__ __forceinline__ float exp_diff(float a, float b) {
    float r;
    asm("ex2.approx.ftz.f32 %0, %1;" : "=f"(r) : "f"((a - b) * 1.4426950408889634f));
    return r;
}
__device__ __forceinline__ float warp_max(float x) {
    int k = __float_as_int(x);
    k ^= (k >> 31) & 0x7fffffff;
    k = __reduce_max_sync(0xffffffffu, k);
    k ^= (k >> 31) & 0x7fffffff;
    return __int_as_float(k);
}
__device__ __forceinline__ float warp_sum(float x) {
#pragma unroll
    for (int o = 16; o > 0; o >>= 1) x += __shfl_xor_sync(0xffffffffu, x, o);
    return x;
}
__device__ __forceinline__ void unpack8(const uint4& v, float* f) {
    f[0] = bf_lo(v.x); f[1] = bf_hi(v.x); f[2] = bf_lo(v.y); f[3] = bf_hi(v.y);
    f[4] = bf_lo(v.z); f[5] = bf_hi(v.z); f[6] = bf_lo(v.w); f[7] = bf_hi(v.w);
}
__device__ __forceinline__ void ln_stats(const uint4& a, const uint4& b, float& mean_bf, float& sd_bf) {
    float f[16];
    unpack8(a, f); unpack8(b, f + 8);
    float s = 0.f;
#pragma unroll
    for (int i = 0; i < 16; i++) s += f[i];
    const float mean = warp_sum(s) * (1.f / DM);
    float q = 0.f;
#pragma unroll
    for (int i = 0; i < 16; i++) { const float d = f[i] - mean; q = fmaf(d, d, q); }
    const float var = warp_sum(q) * (1.f / DM);
    mean_bf = rbf(mean);
    sd_bf = rbf(__fsqrt_rn(rbf(rbf(var) + 1e-5f)));
}
__device__ __forceinline__ float ln_apply(float x, float mean_bf, float sd_bf) {
    return rbf(__fdiv_rn(rbf(x - mean_bf), sd_bf));
}
__device__ __forceinline__ float2 fold8(const float* c) {
    float v[8];
#pragma unroll
    for (int i = 0; i < 8; i++) v[i] = c[2 * i] + c[2 * (i ^ 1) + 1];
    const float w0 = v[0] + __shfl_xor_sync(0xffffffffu, v[2], 1);
    const float w1 = v[1] + __shfl_xor_sync(0xffffffffu, v[3], 1);
    const float w4 = v[4] + __shfl_xor_sync(0xffffffffu, v[6], 1);
    const float w5 = v[5] + __shfl_xor_sync(0xffffffffu, v[7], 1);
    return make_float2(w0 + __shfl_xor_sync(0xffffffffu, w4, 2), w1 + __shfl_xor_sync(0xffffffffu, w5, 2));
}

__device__ __forceinline__ bool needs_float_path(float asum) {
    return !(asum < 0x1p16f) || asum < 0x1p-12f;
}
__device__ __forceinline__ bool add_fixed(unsigned long long* a, __nv_bfloat16* o, long long v, bool skip, float& sum) {
    uint32_t lo = (uint32_t)v, hi = (uint32_t)(v >> 32) + 0x1000000u;
    asm volatile("{\n.reg .pred p;\n.reg .b64 t;\nsetp.eq.u32 p, %3, 0;\nmov.b64 t, {%0, %1};\n"
                 "@p atom.relaxed.gpu.global.add.u64 t, [%2], t;\nmov.b64 {%0, %1}, t;\n}"
                 : "+r"(lo), "+r"(hi) : "l"(a), "r"((uint32_t)skip) : "memory");
    const unsigned long long r = (((unsigned long long)hi << 32) | lo) + ((unsigned long long)v + (1ull << 31) - ((unsigned long long)(NPROD - 1) << 56));
    const uint32_t t = (uint32_t)(r >> 32) + 0x800000u;
    const float frac = (float)(int)((uint32_t)r ^ 0x80000000u);
    const uint32_t pk = pack_bf16(fmaf(frac, 0x1p-32f, (float)(int)(r >> 32)), 0.f);
    asm volatile("{\n.reg .pred p, q;\nsetp.eq.u32 q, %4, 0;\nsetp.lt.and.u32 p, %3, 0x1000000, q;\n"
                 "@p st.global.u16 [%0], %1;\n@p st.global.u64 [%2], 0;\n}"
                 ::"l"(o), "h"((uint16_t)pk), "l"(a), "r"(t), "r"((uint32_t)skip) : "memory");
    sum = fmaf(frac, 0x1p-32f, (float)(int)((uint32_t)(r >> 32) ^ 0x80000000u));
    return (t ^ 0x80000000u) < 0x1000000u;
}
__device__ __noinline__ void finish_flagged(unsigned long long* a, __nv_bfloat16* o, float sum) {
    float side;
    asm volatile("fence.acq_rel.gpu;" ::: "memory");
    asm volatile("atom.relaxed.gpu.global.exch.b32 %0, [%1+8192], 0;" : "=f"(side) : "l"(a) : "memory");
    asm volatile("st.global.u16 [%0], %1;" ::"l"(o), "h"((uint16_t)pack_bf16(sum + side, 0.f)) : "memory");
    asm volatile("st.global.u64 [%0], %1;" ::"l"(a), "l"(0ull) : "memory");
}
__device__ __noinline__ void add_float(unsigned long long* a, __nv_bfloat16* o, float y) {
    asm volatile("red.relaxed.gpu.global.add.f32 [%0+8192], %1;" ::"l"(a), "f"(y) : "memory");
    asm volatile("red.release.gpu.global.or.b64 [%0], %1;" ::"l"(a), "l"(1ull << 63) : "memory");
    float sum;
    if (add_fixed(a, o, 0, false, sum)) finish_flagged(a, o, sum);
}
__device__ __forceinline__ void contribute(unsigned long long* a, __nv_bfloat16* o, float y0, float y1, bool float_path) {
    float sum;
    const bool flagged = add_fixed(a, o, __float2ll_rn(fmaf(y1, 0x1p32f, y0 * 0x1p32f)), float_path, sum);
    if (__builtin_expect(float_path, 0)) add_float(a, o, y0 + y1);
    else if (__builtin_expect(flagged, 0)) finish_flagged(a, o, sum);
}

__global__ void __cluster_dims__(2, 1, 1) __launch_bounds__(NTHREADS, 1)
fused_decode_kernel(const __grid_constant__ Params p, const __grid_constant__ Maps maps) {
    extern __shared__ __align__(1024) unsigned char smem[];
    if (threadIdx.x == 0 && blockIdx.x < NATT) {
        const uint32_t ct = blockIdx.x;
        const char* k0 = (const char*)p.kc + (size_t)((((ct >> 1) & 1) * NH + (ct >> 2)) * SK + (SK - WIN) + (ct & 1) * 64) * (DH * 2);
        asm volatile("cp.async.bulk.prefetch.L2.global.L2::cache_hint [%0], %1, %2;"
                     ::"l"(k0), "r"(STAGE), "l"(policy_evict_first()) : "memory");
    }
    const uint32_t sb = (uint32_t)__cvta_generic_to_shared(smem);
    const uint32_t full0 = sb + OFF_BAR, empty0 = full0 + NST * 8;
    const uint32_t qbar = empty0 + NST * 8, obar = qbar + 8, mlbar = obar + 8;
    const int tid = threadIdx.x, warp = tid >> 5, lane = tid & 31;
    const int cta = blockIdx.x;
    const int g = lane >> 2, c = lane & 3;
    const int r = lane & 7, mi = lane >> 3;
    const bool diag = (c == (g >> 1));

    if (cta < NATT) {
        const int rank = cta & 1, b = (cta >> 1) & 1, h = cta >> 2;
        if (warp == 8) {
            const int row0 = (b * NH + h) * SK + (SK - WIN) + rank * 64;
            const char* kp = (const char*)(p.kc + (size_t)row0 * DH);
            const uint64_t pol = policy_evict_first();
            if (lane == 0) {
#pragma unroll
                for (int s = 0; s < NST; s++) mbar_init(full0 + 8 * s, 1);
                mbar_init_fence();
#pragma unroll
                for (int j = 0; j < PRE; j++) {
                    mbar_expect_tx(full0 + 8 * (4 + j), STAGE);
                    bulk_load(sb + (4 + j) * STAGE, kp + j * (2 * STAGE), STAGE, full0 + 8 * (4 + j), pol);
                }
#pragma unroll
                for (int s = 0; s < 4; s++) {
                    mbar_expect_tx(full0 + 8 * s, STAGE);
                    tensor_load(sb + s * STAGE, &maps.wq, h * DH, rank * 256 + s * 64, full0 + 8 * s);
                }
#pragma unroll
                for (int j = PRE; j < NST - 4; j++) {
                    mbar_expect_tx(full0 + 8 * (4 + j), STAGE);
                    bulk_load(sb + (4 + j) * STAGE, kp + j * (2 * STAGE), STAGE, full0 + 8 * (4 + j), pol);
                }
#pragma unroll
                for (int s = 0; s < NST; s++) mbar_init(empty0 + 8 * s, 8);
                mbar_init(qbar, 1);
                mbar_init(obar, 1 + 8);
                mbar_init(mlbar, 1);
                mbar_init_fence();
                mbar_expect_tx(qbar, 16 * 512);
                mbar_expect_tx(obar, 256);
                mbar_expect_tx(mlbar, 16 * 8);
                prefetch_map(&maps.wo);
                prefetch_map(&maps.v);
            }
            __syncwarp();
            cluster_arrive();
            cluster_wait();
            if (lane == 0) {
                int s = 0, ph = 0;
#pragma unroll 1
                for (int i = NST; i < 72; i++) {
                    mbar_wait_bounded(empty0 + 8 * s, ph);
                    mbar_expect_tx(full0 + 8 * s, STAGE);
                    if (i < 36) bulk_load(sb + s * STAGE, kp + (i - 4) * (2 * STAGE), STAGE, full0 + 8 * s, pol);
                    else if (i < 40) tensor_load(sb + s * STAGE, &maps.wo, rank * 256 + (i - 36) * 64, h * DH, full0 + 8 * s);
                    else tensor_load(sb + s * STAGE, &maps.v, 0, 2 * row0 + (i - 40) * 256, full0 + 8 * s, pol);
                    if (++s == NST) { s = 0; ph ^= 1; }
                }
                mbar_wait_bounded(obar, 0);
            }
        } else {
            const int grp = warp >> 2, w4 = warp & 3;
            const bool e = g & 1;
            uint32_t qf[8][2];
            {
                const __nv_bfloat16* xb = p.x + b * DM;
                const uint4 xs0 = ldg_v4(xb + lane * 16), xs1 = ldg_v4(xb + lane * 16 + 8);
                uint32_t xr[4];
#pragma unroll
                for (int i = 0; i < 4; i++) xr[i] = ldg_u16(xb + rank * 256 + (grp + (i & 2)) * 64 + w4 * 16 + (i & 1) * 8 + g);
                cluster_arrive();
                float mean_bf, sd_bf;
                ln_stats(xs0, xs1, mean_bf, sd_bf);
#pragma unroll
                for (int i = 0; i < 4; i++)
                    xr[i] = diag ? __float_as_uint(ln_apply(bf_lo(xr[i]), mean_bf, sd_bf)) >> (e ? 0 : 16) : 0u;
                float o[8][4];
#pragma unroll
                for (int j = 0; j < 8; j++) { o[j][0] = o[j][1] = o[j][2] = o[j][3] = 0.f; }
                cluster_wait();
#pragma unroll
                for (int t = 0; t < 2; t++) {
                    const int s = grp + 2 * t;
                    const uint32_t wb = sb + s * STAGE + (w4 * 16 + r + 8 * (mi >> 1)) * 256 + (mi & 1) * 128 + r * 16;
                    mbar_wait(full0 + 8 * s, 0);
                    uint32_t a[8][4];
#pragma unroll
                    for (int j = 0; j < 8; j++) ldsm4t(a[j], wb ^ (j << 4));
#pragma unroll
                    for (int j = 0; j < 8; j++) mma16816(o[j], a[j], xr[2 * t], xr[2 * t + 1]);
                    release_stage<2>(empty0 + 8 * s, lane);
                }
                float lo[16], hi[16];
#pragma unroll
                for (int j = 0; j < 8; j++) { lo[2 * j] = o[j][0]; lo[2 * j + 1] = o[j][1]; hi[2 * j] = o[j][2]; hi[2 * j + 1] = o[j][3]; }
                const float2 u0 = fold8(lo), u1 = fold8(hi);
                const uint32_t slot = sb + OFF_QPART + (rank * 8 + warp) * 512 + lane * 16;
                st_async_v4(mapa(slot, 0), u0.x, u0.y, u1.x, u1.y, mapa(qbar, 0));
                st_async_v4(mapa(slot, 1), u0.x, u0.y, u1.x, u1.y, mapa(qbar, 1));
                if (tid < 128) {
                    mbar_wait_cluster(qbar, 0);
                    float sum = 0.f;
#pragma unroll
                    for (int i = 0; i < 16; i++) sum += __uint_as_float(lds_u32(sb + OFF_QPART + i * 512 + tid * 4));
                    const int col = (tid & 2) * 32 + ((tid >> 2) & 3) * 16 + (tid & 1) * 8 + (tid >> 4);
                    sts_u16(sb + OFF_QBF + col * 2, pack_bf16(sum, 0.f));
                }
                bar_sync(1, 256);
#pragma unroll
                for (int j = 0; j < 8; j++) {
                    qf[j][0] = lds_u32(sb + OFF_QBF + ((j ^ g) * 16) + c * 4);
                    qf[j][1] = lds_u32(sb + OFF_QBF + 128 + ((j ^ g) * 16) + c * 4);
                }
            }
            {
                const uint32_t koff = (w4 * 16 + r + 8 * (mi & 1)) * 256 + (mi >> 1) * 128 + r * 16;
                uint32_t sdst = sb + OFF_S + (grp * 64 + w4 * 16 + g) * 2;
                int s = 4 + grp, ph = 0;
#pragma unroll 1
                for (int it = 0; it < 16; it++) {
                    const uint32_t kb = sb + s * STAGE + koff;
                    mbar_wait(full0 + 8 * s, ph);
                    float sa[4] = {0.f, 0.f, 0.f, 0.f}, sc[4] = {0.f, 0.f, 0.f, 0.f};
                    uint32_t a[8][4];
#pragma unroll
                    for (int j = 0; j < 8; j++) ldsm4(a[j], kb ^ (j << 4));
#pragma unroll
                    for (int j = 0; j < 8; j += 2) {
                        mma16816(sa, a[j], qf[j][0], qf[j][1]);
                        mma16816(sc, a[j + 1], qf[j + 1][0], qf[j + 1][1]);
                    }
                    release_stage<2>(empty0 + 8 * s, lane);
                    uint32_t pk = pack_bf16(e ? sa[1] + sc[1] : sa[0] + sc[0], e ? sa[3] + sc[3] : sa[2] + sc[2]);
                    pk = pack_bf16(bf_lo(pk) * 0.08838834764831845f, bf_hi(pk) * 0.08838834764831845f);
                    if (diag) { sts_u16(sdst, pk); sts_u16(sdst + 16, pk >> 16); }
                    sdst += 256;
                    s += 2;
                    if (s >= NST) { s -= NST; ph ^= 1; }
                }
            }
            {
                __syncwarp();
                const int t = (lane & 30) + grp, hf = lane & 1;
                float sv[8];
                unpack8(lds_v4(sb + OFF_S + (t * 64 + w4 * 16 + hf * 8) * 2), sv);
                float m = -3.4028234663852886e38f;
#pragma unroll
                for (int i = 0; i < 8; i++) m = fmaxf(m, sv[i]);
                m = warp_max(m);
                float l = 0.f;
#pragma unroll
                for (int i = 0; i < 8; i++) { sv[i] = exp_diff(sv[i], m); l += sv[i]; }
                l = warp_sum(l);
                if (lane < 2) st_async_v2(mapa(sb + OFF_ML + (rank * 8 + warp) * 8, lane), m, l, mapa(mlbar, lane));
                mbar_wait_cluster(mlbar, 0);
                const float2 ml = lds_f32x2(sb + OFF_ML + (lane & 15) * 8);
                const float M = warp_max(ml.x);
                float L = exp_diff(ml.x, M) * ml.y;
#pragma unroll
                for (int ofs = 8; ofs > 0; ofs >>= 1) L += __shfl_xor_sync(0xffffffffu, L, ofs);
                const float f = __fdiv_rn(exp_diff(m, M), L);
#pragma unroll
                for (int j = 0; j < 4; j++) sts_u32(sb + OFF_P + t * 128 + j * 32 + w4 * 8 + hf * 4, pack_bf16(sv[2 * j] * f, sv[2 * j + 1] * f));
            }
            uint32_t wa[8][2][4];
            {
                const int t4 = 36 + (warp >> 1), st = t4 % NST, jr = 4 * (mi >> 1) + (r >> 1);
                mbar_wait(full0 + 8 * st, (t4 / NST) & 1);
                const uint32_t wb = sb + st * STAGE + (8 * (r & 1) + jr) * 128 + ((4 * (warp & 1) + (mi & 1)) ^ jr) * 16;
#pragma unroll
                for (int t = 0; t < 8; t++)
#pragma unroll
                    for (int j = 0; j < 2; j++) ldsm4t(wa[t][j], (wb ^ (j << 5)) + t * 2048);
                release_stage<4>(empty0 + 8 * st, lane);
            }
            const uint32_t vbase = pin(sb + (8 * (mi >> 1) + r) * 256 + grp * 128 + ((2 * w4) ^ (mi & 1) ^ (r >> 2) ^ (2 * (r & 3) + grp)) * 16);
            const uint32_t o_loc = pin(sb + OFF_OPART + (warp >> 1) * 128 + rank * 64 + (g & 3) * 16 + (warp & 1) * 8 + (g >> 2) * 4);
            const uint32_t o_dst = pin(mapa(o_loc, rank ^ 1)), o_bar = pin(mapa(obar + c * 8, rank ^ 1));
            const uint32_t o_src = pin(sb + OFF_OPART + (g & 1) * 64 + c * 16), obar_p = pin(obar);
            const uint32_t first = pin((uint32_t)(c == 0));
            const bool lane0 = pin((uint32_t)(lane == 0)), odd = pin((uint32_t)(c & 1));
            unsigned long long* const acc_p = pin(p.acc + b * DM + rank * 256 + tid);
            __nv_bfloat16* const out_p = pin(p.out + b * DM + rank * 256 + warp * 32 + c * 8 + g);
            const bool feed = pin((uint32_t)((c >> 1) == (g & 1))), low = pin((uint32_t)(c < 2));
            bar_sync(1, 256);
            float oc[4][4];
#pragma unroll
            for (int j = 0; j < 4; j++) { oc[j][0] = oc[j][1] = oc[j][2] = oc[j][3] = 0.f; }
            {
                auto pv_tile = [&](uint32_t vb, const uint4& p0, const uint4& p1) {
                    uint32_t a[4][4];
#pragma unroll
                    for (int j = 0; j < 4; j++) ldsm4t(a[j], vb + j * 4096);
                    mma16816(oc[0], a[0], p0.x, p0.y);
                    mma16816(oc[1], a[1], p0.z, p0.w);
                    mma16816(oc[2], a[2], p1.x, p1.y);
                    mma16816(oc[3], a[3], p1.z, p1.w);
                };
                uint32_t psrc = sb + OFF_P + c * 32;
                uint4 pe[EG][2];
#pragma unroll
                for (int j = 0; j < EG; j++) {
                    pe[j][0] = pe[j][1] = make_uint4(0u, 0u, 0u, 0u);
                    if (feed) { pe[j][0] = lds_v4(psrc + (32 - EG + j) * 128); pe[j][1] = lds_v4(psrc + (32 - EG + j) * 128 + 16); }
                }
                int s = 40 % NST, ph = (40 / NST) & 1;
#pragma unroll 1
                for (int it = 0; it < 32 - EG; it++) {
                    uint4 p0 = make_uint4(0u, 0u, 0u, 0u), p1 = p0;
                    if (feed) { p0 = lds_v4(psrc); p1 = lds_v4(psrc + 16); }
                    psrc += 128;
                    mbar_wait(full0 + 8 * s, ph);
                    pv_tile(vbase + s * STAGE, p0, p1);
                    if (it < 32 - NST) release_stage<1>(empty0 + 8 * s, lane);
                    if (++s == NST) { s = 0; ph ^= 1; }
                }
#pragma unroll
                for (int j = 0; j < EG; j++) {
                    mbar_wait(full0 + 8 * (NST - EG + j), (72 / NST - 1) & 1);
                    pv_tile(vbase + (NST - EG + j) * STAGE, pe[j][0], pe[j][1]);
                }
            }
            const uint32_t opk = pack_bf16(
                (((oc[0][0] + oc[0][3]) + (oc[1][0] + oc[1][3])) + (oc[2][0] + oc[2][3])) + (oc[3][0] + oc[3][3]),
                (((oc[0][1] + oc[0][2]) + (oc[1][1] + oc[1][2])) + (oc[2][1] + oc[2][2])) + (oc[3][1] + oc[3][2]));
            asm volatile("{\n.reg .pred p;\nsetp.ne.u32 p, %4, 0;\n"
                         "@p st.async.shared::cluster.mbarrier::complete_tx::bytes.u32 [%0], %1, [%2];\n@p st.shared.u32 [%3], %1;\n}"
                         ::"r"(o_dst), "r"(opk), "r"(o_bar), "r"(o_loc), "r"(first) : "memory");
            __syncwarp();
            if (lane0) mbar_arrive<1>(obar_p);
            mbar_wait(obar_p, 0);
            float y0[4] = {0.f, 0.f, 0.f, 0.f}, y1[4] = {0.f, 0.f, 0.f, 0.f};
            uint4 of[4];
#pragma unroll
            for (int j = 0; j < 4; j++) of[j] = lds_v4(o_src + j * 128);
#pragma unroll
            for (int j = 0; j < 4; j++) {
                mma16816(y0, wa[2 * j][0], of[j].x, of[j].y);
                mma16816(y1, wa[2 * j][1], of[j].x, of[j].y);
                mma16816(y0, wa[2 * j + 1][0], of[j].z, of[j].w);
                mma16816(y1, wa[2 * j + 1][1], of[j].z, of[j].w);
            }
            const float z0 = odd ? y0[2] : y0[0], z1 = odd ? y0[3] : y0[1];
            const float z2 = odd ? y1[2] : y1[0], z3 = odd ? y1[3] : y1[1];
            const float asum = ((fabsf(y0[0]) + fabsf(y0[1])) + (fabsf(y0[2]) + fabsf(y0[3]))) +
                               ((fabsf(y1[0]) + fabsf(y1[1])) + (fabsf(y1[2]) + fabsf(y1[3])));
            contribute(acc_p, out_p, low ? z0 : z2, low ? z1 : z3, needs_float_path(asum));
        }
    } else {
        const int fj = cta - NATT;
        const int sh1 = fj & 1;
        const int T1 = 32 + sh1, T2 = (fj == NFFN - 1) ? (FF - (NFFN - 1) * FSL) / 16 : FSL / 16;
        uint4 xs0, xs1;
        uint32_t bias_raw[6], res_raw[6];
        if (warp < 8) {
            xs0 = ldg_v4(p.x + (warp & 1) * DM + lane * 16);
            xs1 = ldg_v4(p.x + (warp & 1) * DM + lane * 16 + 8);
#pragma unroll
            for (int j = 0; j < 6; j++) bias_raw[j] = ldg_u16(p.b1 + min(fj * FSL + (warp + 8 * (j >> 1)) * 16 + (j & 1) * 8 + g, FF - 1));
#pragma unroll
            for (int j = 0; j < 6; j++) res_raw[j] = ldg_u16((j < 4 ? p.x + (j >> 1) * DM : p.b2) + warp * 64 + c * 16 + (j & 1) * 8 + g);
        } else if (lane == 0) {
            prefetch_map(&maps.w1);
#pragma unroll
            for (int s = 0; s < NST; s++) { mbar_init(full0 + 8 * s, 1); mbar_init(empty0 + 8 * s, 8); }
            mbar_init_fence();
        }
        __syncthreads();
        if (warp == 8) {
            if (lane == 0) {
                const char* p2 = (const char*)(p.w2 + (size_t)fj * FSL * DM);
                const uint64_t pol = policy_evict_first();
                int s = 0, ph = 1;
#pragma unroll 1
                for (int i = 0; i < T1 + T2 + NST; i++) {
                    mbar_wait_bounded(empty0 + 8 * s, ph);
                    if (i < T1) {
                        mbar_expect_tx(full0 + 8 * s, 16 * FSL * 2);
                        tensor_load(sb + s * STAGE, &maps.w1, fj * (FSL / 2), i * 16 - sh1, full0 + 8 * s, pol);
                    } else if (i < T1 + T2) {
                        mbar_expect_tx(full0 + 8 * s, STAGE);
                        bulk_load(sb + s * STAGE, p2 + (size_t)(i - T1) * STAGE, STAGE, full0 + 8 * s, pol);
                    }
                    if (++s == NST) { s = 0; ph ^= 1; }
                }
            }
        } else {
            const uint32_t xn_s = sb + OFF_QPART;
            const uint32_t g_s = xn_s + 2 * 1056;
            if (warp < 2) {
                float mean_bf, sd_bf, xn[16];
                ln_stats(xs0, xs1, mean_bf, sd_bf);
                unpack8(xs0, xn); unpack8(xs1, xn + 8);
#pragma unroll
                for (int i = 0; i < 16; i++) sts_u16(xn_s + warp * 1056 + (lane * 16 + i + sh1) * 2, pack_bf16(ln_apply(xn[i], mean_bf, sd_bf), 0.f));
                if (lane < 16) sts_u16(xn_s + warp * 1056 + (lane == 15 && sh1 ? 0 : DM + sh1 + lane) * 2, 0);
            }
            bar_sync(1, 256);
            int s = 0, ph = 0;
            float hacc[3][4];
#pragma unroll
            for (int j = 0; j < 3; j++) { hacc[j][0] = hacc[j][1] = hacc[j][2] = hacc[j][3] = 0.f; }
            uint32_t aoff[3];
#pragma unroll
            for (int j = 0; j < 3; j++) aoff[j] = (r + 8 * (mi >> 1)) * (FSL * 2) + min(2 * (warp + 8 * j) + (mi & 1), FSL / 8 - 1) * 16;
#pragma unroll 1
            for (int i = 0; i < T1; i++) {
                uint32_t f0 = 0, f1 = 0;
                if (g < 2) { f0 = lds_u32(xn_s + g * 1056 + i * 32 + c * 4); f1 = lds_u32(xn_s + g * 1056 + i * 32 + 16 + c * 4); }
                mbar_wait(full0 + 8 * s, ph);
#pragma unroll
                for (int j = 0; j < 3; j++) {
                    uint32_t a[4];
                    ldsm4t(a, sb + s * STAGE + aoff[j]);
                    mma16816(hacc[j], a, f0, f1);
                }
                release_stage<1>(empty0 + 8 * s, lane);
                if (++s == NST) { s = 0; ph ^= 1; }
            }
            if (c == 0) {
#pragma unroll
                for (int j = 0; j < 3; j++)
#pragma unroll
                    for (int hf = 0; hf < 2; hf++) {
                        const int f = (warp + 8 * j) * 16 + hf * 8 + g;
                        if (f < FSL) {
                            const float bias = bf_lo(bias_raw[2 * j + hf]);
#pragma unroll
                            for (int bb = 0; bb < 2; bb++) {
                                const float hv = rbf(rbf(hacc[j][2 * hf + bb]) + bias);
                                const float inner = 0.7978845608028654f * (hv + 0.044715f * hv * hv * hv);
                                sts_u16(g_s + bb * 704 + f * 2, pack_bf16(0.5f * hv * (1.f + tanhf(inner)), 0.f));
                            }
                        }
                    }
            }
            bar_sync(1, 256);
            float y[2][4][4];
#pragma unroll
            for (int bb = 0; bb < 2; bb++)
#pragma unroll
                for (int j = 0; j < 4; j++) { y[bb][j][0] = y[bb][j][1] = y[bb][j][2] = y[bb][j][3] = 0.f; }
            const int sh = (g & 1) * 16;
#pragma unroll 1
            for (int i = 0; i < T2; i++) {
                uint32_t f[2][2] = {{0u, 0u}, {0u, 0u}};
                if (diag) {
#pragma unroll
                    for (int bb = 0; bb < 2; bb++) {
                        f[bb][0] = lds_u16(g_s + bb * 704 + (i * 16 + g) * 2) << sh;
                        f[bb][1] = lds_u16(g_s + bb * 704 + (i * 16 + 8 + g) * 2) << sh;
                    }
                }
                const uint32_t wb = sb + s * STAGE + (r + 8 * (mi >> 1)) * 1024 + warp * 128 + (((mi & 1) * 4) ^ r) * 16;
                mbar_wait(full0 + 8 * s, ph);
#pragma unroll
                for (int j = 0; j < 4; j++) {
                    uint32_t a[4];
                    ldsm4t(a, wb ^ (j << 4));
                    mma16816(y[0][j], a, f[0][0], f[0][1]);
                    mma16816(y[1][j], a, f[1][0], f[1][1]);
                }
                release_stage<1>(empty0 + 8 * s, lane);
                if (++s == NST) { s = 0; ph ^= 1; }
            }
#pragma unroll
            for (int bb = 0; bb < 2; bb++) {
                float yy[16];
#pragma unroll
                for (int j = 0; j < 4; j++) { yy[2 * j] = y[bb][j][0]; yy[2 * j + 1] = y[bb][j][1]; yy[8 + 2 * j] = y[bb][j][2]; yy[8 + 2 * j + 1] = y[bb][j][3]; }
                float2 yo = fold8(yy);
                if (fj == 0) {
                    yo.x += bf_lo(res_raw[2 * bb]) + bf_lo(res_raw[4]);
                    yo.y += bf_lo(res_raw[2 * bb + 1]) + bf_lo(res_raw[5]);
                }
                const int n0 = bb * DM + warp * 64 + c * 16;
                unsigned long long* a = p.acc + (n0 & ~31) + 4 * g + 2 * (c & 1);
                const bool fp = needs_float_path(warp_sum(fabsf(yo.x) + fabsf(yo.y)));
                contribute(a, p.out + n0 + g, yo.x, 0.f, fp);
                contribute(a + 1, p.out + n0 + 8 + g, yo.y, 0.f, fp);
            }
        }
    }
}

typedef CUresult (*EncodeFn)(CUtensorMap*, CUtensorMapDataType, cuuint32_t, void*, const cuuint64_t*, const cuuint64_t*,
                             const cuuint32_t*, const cuuint32_t*, CUtensorMapInterleave, CUtensorMapSwizzle,
                             CUtensorMapL2promotion, CUtensorMapFloatOOBfill);

void encode_2d(EncodeFn fn, CUtensorMap* map, CUtensorMapDataType dt, const void* base, uint64_t cols, uint64_t rows,
               uint64_t pitch_bytes, uint32_t box_cols, uint32_t box_rows, CUtensorMapSwizzle sw) {
    const cuuint64_t dims[2] = {cols, rows}, strides[1] = {pitch_bytes};
    const cuuint32_t box[2] = {box_cols, box_rows}, estr[2] = {1, 1};
    fn(map, dt, 2, const_cast<void*>(base), dims, strides, box, estr, CU_TENSOR_MAP_INTERLEAVE_NONE, sw,
       CU_TENSOR_MAP_L2_PROMOTION_NONE, CU_TENSOR_MAP_FLOAT_OOB_FILL_NONE);
}

}

extern "C" void kernel_launch(void* const* d_in, const int* in_sizes, int n_in, void* d_out, int out_size) {
    (void)in_sizes; (void)n_in; (void)out_size;
    typedef const __nv_bfloat16* P;
    static EncodeFn encode = nullptr;
    static void* acc = nullptr;
    if (!encode) {
        cudaFuncSetAttribute(fused_decode_kernel, cudaFuncAttributeMaxDynamicSharedMemorySize, SMEM_BYTES);
        cudaDriverEntryPointQueryResult st;
        cudaGetDriverEntryPoint("cuTensorMapEncodeTiled", (void**)&encode, cudaEnableDefault, &st);
        cudaGetSymbolAddress(&acc, g_acc);
    }
    Params p;
    p.kc = (P)d_in[1]; p.x = (P)d_in[0];
    p.acc = (unsigned long long*)acc; p.out = (__nv_bfloat16*)d_out;
    p.w2 = (P)d_in[8]; p.b1 = (P)d_in[7]; p.b2 = (P)d_in[9];
    Maps maps;
    encode_2d(encode, &maps.wq, CU_TENSOR_MAP_DATA_TYPE_BFLOAT16, d_in[3], NH * DH, DM, NH * DH * 2, DH, 64,
              CU_TENSOR_MAP_SWIZZLE_NONE);
    encode_2d(encode, &maps.v, CU_TENSOR_MAP_DATA_TYPE_BFLOAT16, d_in[2], 64, (uint64_t)2 * 2 * NH * SK, 128, 64, 128,
              CU_TENSOR_MAP_SWIZZLE_128B);
    encode_2d(encode, &maps.wo, CU_TENSOR_MAP_DATA_TYPE_BFLOAT16, d_in[4], DM, NH * DH, DM * 2, 64, 128,
              CU_TENSOR_MAP_SWIZZLE_128B);
    encode_2d(encode, &maps.w1, CU_TENSOR_MAP_DATA_TYPE_UINT32, d_in[6], FF / 2, DM, FF * 2, FSL / 2, 16,
              CU_TENSOR_MAP_SWIZZLE_NONE);
    fused_decode_kernel<<<NCTA, NTHREADS, SMEM_BYTES>>>(p, maps);
}
```

```cpp
#include <cuda.h>
#include <cuda_runtime.h>
#include <cuda_bf16.h>
#include <stdint.h>

namespace {

constexpr int DM = 512, NH = 32, SK = 16384, WIN = 4096, DH = 128, FF = 1376;
constexpr int NATT = 128, NFFN = 4, NCTA = NATT + NFFN;
constexpr int NPROD = NH + NFFN;
constexpr int FSL = 352;
constexpr int NST = 8;
constexpr int STAGE = 16384;
constexpr int PRE = 2;
constexpr int EG = 4;
constexpr int NTHREADS = 288;
static_assert(NST % 2 == 0 && 72 % NST == 0 && EG <= NST, "ring geometry");

constexpr int OFF_QPART = NST * STAGE;
constexpr int OFF_S = OFF_QPART, OFF_P = OFF_QPART + 4096;
constexpr int OFF_OPART = OFF_QPART + 8192;
constexpr int OFF_ML = OFF_OPART + 512;
constexpr int OFF_QBF = OFF_ML + 128;
constexpr int OFF_BAR = OFF_QBF + 256;
constexpr int SMEM_BYTES = OFF_BAR + (2 * NST + 3) * 8;

__device__ __align__(256) unsigned long long g_acc[2 * 2 * DM];

struct Params {
    const __nv_bfloat16 *kc, *x;
    unsigned long long* acc;
    __nv_bfloat16* out;
    const __nv_bfloat16 *w2, *b1, *b2;
};
struct Maps {
    alignas(64) CUtensorMap wq, v, wo, w1;
};

__device__ __forceinline__ void mbar_init(uint32_t bar, uint32_t cnt) {
    asm volatile("mbarrier.init.shared::cta.b64 [%0], %1;" ::"r"(bar), "r"(cnt) : "memory");
}
__device__ __forceinline__ void mbar_init_fence() { asm volatile("fence.mbarrier_init.release.cluster;" ::: "memory"); }
__device__ __forceinline__ void mbar_expect_tx(uint32_t bar, uint32_t bytes) {
    asm volatile("mbarrier.arrive.expect_tx.shared::cta.b64 _, [%0], %1;" ::"r"(bar), "r"(bytes) : "memory");
}
template <int N>
__device__ __forceinline__ void mbar_arrive(uint32_t bar) {
    asm volatile("mbarrier.arrive.shared::cta.b64 _, [%0], %1;" ::"r"(bar), "n"(N) : "memory");
}
template <int N>
__device__ __forceinline__ void release_stage(uint32_t bar, int lane) {
    asm volatile("fence.proxy.async.shared::cta;" ::: "memory");
    __syncwarp();
    if (lane == 0) mbar_arrive<N>(bar);
}
#define WAIT_LIMIT (1u << 18)
__device__ __forceinline__ void mbar_wait_bounded(uint32_t bar, uint32_t parity) {
    uint32_t ok, n = 0;
    do {
        if (++n > WAIT_LIMIT) __trap();
        asm volatile(
            "{\n.reg .pred p;\nmbarrier.try_wait.parity.shared::cta.b64 p, [%1], %2;\nselp.u32 %0, 1, 0, p;\n}\n"
            : "=r"(ok) : "r"(bar), "r"(parity) : "memory");
    } while (!ok);
}
__device__ __forceinline__ void mbar_wait(uint32_t bar, uint32_t parity) {
    asm volatile(
        "{\n.reg .pred p;\nWAIT_LOOP:\nmbarrier.try_wait.parity.shared::cta.b64 p, [%0], %1;\n@!p bra WAIT_LOOP;\n}\n"
        ::"r"(bar), "r"(parity) : "memory");
}
__device__ __forceinline__ void mbar_wait_cluster(uint32_t bar, uint32_t parity) {
    asm volatile(
        "{\n.reg .pred p;\nWAIT_LOOP:\nmbarrier.try_wait.parity.acquire.cluster.shared::cta.b64 p, [%0], %1;\n@!p bra WAIT_LOOP;\n}\n"
        ::"r"(bar), "r"(parity) : "memory");
}
__device__ __forceinline__ uint64_t policy_evict_first() {
    uint64_t pol;
    asm volatile("createpolicy.fractional.L2::evict_first.b64 %0, 1.0;" : "=l"(pol));
    return pol;
}
__device__ __forceinline__ void bulk_load(uint32_t dst, const void* src, uint32_t bytes, uint32_t bar, uint64_t pol) {
    asm volatile("cp.async.bulk.shared::cluster.global.mbarrier::complete_tx::bytes.L2::cache_hint [%0], [%1], %2, [%3], %4;"
                 ::"r"(dst), "l"(src), "r"(bytes), "r"(bar), "l"(pol) : "memory");
}
__device__ __forceinline__ void tensor_load(uint32_t dst, const CUtensorMap* map, int cx, int cy, uint32_t bar) {
    asm volatile("cp.async.bulk.tensor.2d.shared::cluster.global.mbarrier::complete_tx::bytes [%0], [%1, {%2, %3}], [%4];"
                 ::"r"(dst), "l"(map), "r"(cx), "r"(cy), "r"(bar) : "memory");
}
__device__ __forceinline__ void tensor_load(uint32_t dst, const CUtensorMap* map, int cx, int cy, uint32_t bar, uint64_t pol) {
    asm volatile("cp.async.bulk.tensor.2d.shared::cluster.global.mbarrier::complete_tx::bytes.L2::cache_hint [%0], [%1, {%2, %3}], [%4], %5;"
                 ::"r"(dst), "l"(map), "r"(cx), "r"(cy), "r"(bar), "l"(pol) : "memory");
}
__device__ __forceinline__ void prefetch_map(const CUtensorMap* map) {
    asm volatile("prefetch.tensormap [%0];" ::"l"(map) : "memory");
}
__device__ __forceinline__ uint4 ldg_v4(const void* p) {
    uint4 v;
    asm volatile("ld.global.v4.u32 {%0,%1,%2,%3}, [%4];" : "=r"(v.x), "=r"(v.y), "=r"(v.z), "=r"(v.w) : "l"(p) : "memory");
    return v;
}
__device__ __forceinline__ uint32_t ldg_u16(const void* p) {
    uint16_t v;
    asm volatile("ld.global.u16 %0, [%1];" : "=h"(v) : "l"(p) : "memory");
    return v;
}
__device__ __forceinline__ void ldsm4(uint32_t (&r)[4], uint32_t addr) {
    asm volatile("ldmatrix.sync.aligned.m8n8.x4.shared.b16 {%0,%1,%2,%3}, [%4];"
                 : "=r"(r[0]), "=r"(r[1]), "=r"(r[2]), "=r"(r[3]) : "r"(addr) : "memory");
}
__device__ __forceinline__ void ldsm4t(uint32_t (&r)[4], uint32_t addr) {
    asm volatile("ldmatrix.sync.aligned.m8n8.x4.trans.shared.b16 {%0,%1,%2,%3}, [%4];"
                 : "=r"(r[0]), "=r"(r[1]), "=r"(r[2]), "=r"(r[3]) : "r"(addr) : "memory");
}
__device__ __forceinline__ void mma16816(float (&d)[4], const uint32_t (&a)[4], uint32_t b0, uint32_t b1) {
    asm volatile(
        "mma.sync.aligned.m16n8k16.row.col.f32.bf16.bf16.f32 {%0,%1,%2,%3}, {%4,%5,%6,%7}, {%8,%9}, {%0,%1,%2,%3};"
        : "+f"(d[0]), "+f"(d[1]), "+f"(d[2]), "+f"(d[3])
        : "r"(a[0]), "r"(a[1]), "r"(a[2]), "r"(a[3]), "r"(b0), "r"(b1));
}
__device__ __forceinline__ uint32_t mapa(uint32_t addr, uint32_t rank) {
    uint32_t r;
    asm("mapa.shared::cluster.u32 %0, %1, %2;" : "=r"(r) : "r"(addr), "r"(rank));
    return r;
}
__device__ __forceinline__ void st_async_v4(uint32_t addr, float a, float b, float c, float d, uint32_t bar) {
    asm volatile("st.async.shared::cluster.mbarrier::complete_tx::bytes.v4.f32 [%0], {%1,%2,%3,%4}, [%5];"
                 ::"r"(addr), "f"(a), "f"(b), "f"(c), "f"(d), "r"(bar) : "memory");
}
__device__ __forceinline__ void st_async_v2(uint32_t addr, float a, float b, uint32_t bar) {
    asm volatile("st.async.shared::cluster.mbarrier::complete_tx::bytes.v2.f32 [%0], {%1,%2}, [%3];"
                 ::"r"(addr), "f"(a), "f"(b), "r"(bar) : "memory");
}
__device__ __forceinline__ uint32_t lds_u16(uint32_t addr) {
    uint16_t v;
    asm volatile("ld.shared.u16 %0, [%1];" : "=h"(v) : "r"(addr) : "memory");
    return v;
}
__device__ __forceinline__ uint32_t lds_u32(uint32_t addr) {
    uint32_t v;
    asm volatile("ld.shared.u32 %0, [%1];" : "=r"(v) : "r"(addr) : "memory");
    return v;
}
__device__ __forceinline__ float2 lds_f32x2(uint32_t addr) {
    float2 v;
    asm volatile("ld.shared.v2.f32 {%0,%1}, [%2];" : "=f"(v.x), "=f"(v.y) : "r"(addr) : "memory");
    return v;
}
__device__ __forceinline__ uint4 lds_v4(uint32_t addr) {
    uint4 v;
    asm volatile("ld.shared.v4.u32 {%0,%1,%2,%3}, [%4];" : "=r"(v.x), "=r"(v.y), "=r"(v.z), "=r"(v.w) : "r"(addr) : "memory");
    return v;
}
__device__ __forceinline__ void sts_u16(uint32_t addr, uint32_t v) {
    asm volatile("st.shared.u16 [%0], %1;" ::"r"(addr), "h"((uint16_t)v) : "memory");
}
__device__ __forceinline__ void sts_u32(uint32_t addr, uint32_t v) {
    asm volatile("st.shared.u32 [%0], %1;" ::"r"(addr), "r"(v) : "memory");
}
__device__ __forceinline__ void bar_sync(int id, int n) { asm volatile("bar.sync %0, %1;" ::"r"(id), "r"(n) : "memory"); }
__device__ __forceinline__ void cluster_arrive() { asm volatile("barrier.cluster.arrive.relaxed.aligned;" ::: "memory"); }
__device__ __forceinline__ void cluster_wait() { asm volatile("barrier.cluster.wait.acquire.aligned;" ::: "memory"); }

__device__ __forceinline__ uint32_t pin(uint32_t v) { return __shfl_sync(0xffffffffu, v, threadIdx.x & 31); }
template <class T>
__device__ __forceinline__ T* pin(T* q) {
    const uint64_t v = (uint64_t)q;
    return (T*)(((uint64_t)pin((uint32_t)(v >> 32)) << 32) | pin((uint32_t)v));
}

__device__ __forceinline__ uint32_t pack_bf16(float lo, float hi) {
    uint32_t r;
    asm("cvt.rn.bf16x2.f32 %0, %1, %2;" : "=r"(r) : "f"(hi), "f"(lo));
    return r;
}
__device__ __forceinline__ float bf_lo(uint32_t v) { return __uint_as_float(v << 16); }
__device__ __forceinline__ float bf_hi(uint32_t v) { return __uint_as_float(v & 0xffff0000u); }
__device__ __forceinline__ float rbf(float x) { return bf_lo(pack_bf16(x, 0.f)); }
__device__ __forceinline__ float exp_diff(float a, float b) {
    float r;
    asm("ex2.approx.ftz.f32 %0, %1;" : "=f"(r) : "f"((a - b) * 1.4426950408889634f));
    return r;
}
__device__ __forceinline__ float warp_max(float x) {
    int k = __float_as_int(x);
    k ^= (k >> 31) & 0x7fffffff;
    k = __reduce_max_sync(0xffffffffu, k);
    k ^= (k >> 31) & 0x7fffffff;
    return __int_as_float(k);
}
__device__ __forceinline__ float warp_sum(float x) {
#pragma unroll
    for (int o = 16; o > 0; o >>= 1) x += __shfl_xor_sync(0xffffffffu, x, o);
    return x;
}
__device__ __forceinline__ void unpack8(const uint4& v, float* f) {
    f[0] = bf_lo(v.x); f[1] = bf_hi(v.x); f[2] = bf_lo(v.y); f[3] = bf_hi(v.y);
    f[4] = bf_lo(v.z); f[5] = bf_hi(v.z); f[6] = bf_lo(v.w); f[7] = bf_hi(v.w);
}
__device__ __forceinline__ void ln_stats(const uint4& a, const uint4& b, float& mean_bf, float& sd_bf) {
    float f[16];
    unpack8(a, f); unpack8(b, f + 8);
    float s = 0.f;
#pragma unroll
    for (int i = 0; i < 16; i++) s += f[i];
    const float mean = warp_sum(s) * (1.f / DM);
    float q = 0.f;
#pragma unroll
    for (int i = 0; i < 16; i++) { const float d = f[i] - mean; q = fmaf(d, d, q); }
    const float var = warp_sum(q) * (1.f / DM);
    mean_bf = rbf(mean);
    sd_bf = rbf(__fsqrt_rn(rbf(rbf(var) + 1e-5f)));
}
__device__ __forceinline__ float ln_apply(float x, float mean_bf, float sd_bf) {
    return rbf(__fdiv_rn(rbf(x - mean_bf), sd_bf));
}
__device__ __forceinline__ float2 fold8(const float* c) {
    float v[8];
#pragma unroll
    for (int i = 0; i < 8; i++) v[i] = c[2 * i] + c[2 * (i ^ 1) + 1];
    const float w0 = v[0] + __shfl_xor_sync(0xffffffffu, v[2], 1);
    const float w1 = v[1] + __shfl_xor_sync(0xffffffffu, v[3], 1);
    const float w4 = v[4] + __shfl_xor_sync(0xffffffffu, v[6], 1);
    const float w5 = v[5] + __shfl_xor_sync(0xffffffffu, v[7], 1);
    return make_float2(w0 + __shfl_xor_sync(0xffffffffu, w4, 2), w1 + __shfl_xor_sync(0xffffffffu, w5, 2));
}

__device__ __forceinline__ bool needs_float_path(float mag) {
    return !(mag < 0x1p13f) || mag < 0x1p-12f;
}
__device__ __forceinline__ bool add_fixed(unsigned long long* a, __nv_bfloat16* o, long long v, bool skip, float& sum) {
    uint32_t lo = (uint32_t)v, hi = (uint32_t)(v >> 32) + 0x1000000u;
    asm volatile("{\n.reg .pred p;\n.reg .b64 t;\nsetp.eq.u32 p, %3, 0;\nmov.b64 t, {%0, %1};\n"
                 "@p atom.relaxed.gpu.global.add.u64 t, [%2], t;\nmov.b64 {%0, %1}, t;\n}"
                 : "+r"(lo), "+r"(hi) : "l"(a), "r"((uint32_t)skip) : "memory");
    const unsigned long long r = (((unsigned long long)hi << 32) | lo) + ((unsigned long long)v + (1ull << 31) - ((unsigned long long)(NPROD - 1) << 56));
    const uint32_t t = (uint32_t)(r >> 32) + 0x800000u;
    const float frac = (float)(int)((uint32_t)r ^ 0x80000000u) * 0x1p-36f;
    const uint32_t pk = pack_bf16(fmaf((float)(int)(r >> 32), 0x1p-4f, frac), 0.f);
    asm volatile("{\n.reg .pred p, q;\nsetp.eq.u32 q, %4, 0;\nsetp.lt.and.u32 p, %3, 0x1000000, q;\n"
                 "@p st.global.u16 [%0], %1;\n@p st.global.u64 [%2], 0;\n}"
                 ::"l"(o), "h"((uint16_t)pk), "l"(a), "r"(t), "r"((uint32_t)skip) : "memory");
    sum = fmaf((float)(int)((uint32_t)(r >> 32) ^ 0x80000000u), 0x1p-4f, frac);
    return (t ^ 0x80000000u) < 0x1000000u;
}
__device__ __noinline__ void finish_flagged(unsigned long long* a, __nv_bfloat16* o, float sum) {
    float side;
    asm volatile("fence.acq_rel.gpu;" ::: "memory");
    asm volatile("atom.relaxed.gpu.global.exch.b32 %0, [%1+8192], 0;" : "=f"(side) : "l"(a) : "memory");
    asm volatile("st.global.u16 [%0], %1;" ::"l"(o), "h"((uint16_t)pack_bf16(sum + side, 0.f)) : "memory");
    asm volatile("st.global.u64 [%0], %1;" ::"l"(a), "l"(0ull) : "memory");
}
__device__ __noinline__ void add_float(unsigned long long* a, __nv_bfloat16* o, float y) {
    asm volatile("red.relaxed.gpu.global.add.f32 [%0+8192], %1;" ::"l"(a), "f"(y) : "memory");
    asm volatile("red.release.gpu.global.or.b64 [%0], %1;" ::"l"(a), "l"(1ull << 63) : "memory");
    float sum;
    if (add_fixed(a, o, 0, false, sum)) finish_flagged(a, o, sum);
}
__device__ __forceinline__ void contribute(unsigned long long* a, __nv_bfloat16* o, float y0, float y1, bool float_path) {
    float sum;
    const bool flagged = add_fixed(a, o, __float2ll_rn(fmaf(y1, 0x1p36f, y0 * 0x1p36f)), float_path, sum);
    if (__builtin_expect(float_path, 0)) add_float(a, o, y0 + y1);
    else if (__builtin_expect(flagged, 0)) finish_flagged(a, o, sum);
}

__global__ void __cluster_dims__(2, 1, 1) __launch_bounds__(NTHREADS, 1)
fused_decode_kernel(const __grid_constant__ Params p, const __grid_constant__ Maps maps) {
    extern __shared__ __align__(1024) unsigned char smem[];
    if (threadIdx.x == 0 && blockIdx.x < NATT) {
        const uint32_t ct = blockIdx.x;
        const char* k0 = (const char*)p.kc + (size_t)((((ct >> 1) & 1) * NH + (ct >> 2)) * SK + (SK - WIN) + (ct & 1) * 64) * (DH * 2);
        asm volatile("cp.async.bulk.prefetch.L2.global.L2::cache_hint [%0], %1, %2;"
                     ::"l"(k0), "r"(STAGE), "l"(policy_evict_first()) : "memory");
    }
    const uint32_t sb = (uint32_t)__cvta_generic_to_shared(smem);
    const uint32_t full0 = sb + OFF_BAR, empty0 = full0 + NST * 8;
    const uint32_t qbar = empty0 + NST * 8, obar = qbar + 8, mlbar = obar + 8;
    const int tid = threadIdx.x, warp = tid >> 5, lane = tid & 31;
    const int cta = blockIdx.x;
    const int g = lane >> 2, c = lane & 3;
    const int r = lane & 7, mi = lane >> 3;
    const bool diag = (c == (g >> 1));

    if (cta < NATT) {
        const int rank = cta & 1, b = (cta >> 1) & 1, h = cta >> 2;
        if (warp == 8) {
            const int row0 = (b * NH + h) * SK + (SK - WIN) + rank * 64;
            const char* kp = (const char*)(p.kc + (size_t)row0 * DH);
            const uint64_t pol = policy_evict_first();
            if (lane == 0) {
#pragma unroll
                for (int s = 0; s < NST; s++) mbar_init(full0 + 8 * s, 1);
                mbar_init_fence();
#pragma unroll
                for (int j = 0; j < PRE; j++) {
                    mbar_expect_tx(full0 + 8 * (4 + j), STAGE);
                    bulk_load(sb + (4 + j) * STAGE, kp + j * (2 * STAGE), STAGE, full0 + 8 * (4 + j), pol);
                }
#pragma unroll
                for (int s = 0; s < 4; s++) {
                    mbar_expect_tx(full0 + 8 * s, STAGE);
                    tensor_load(sb + s * STAGE, &maps.wq, h * DH, rank * 256 + s * 64, full0 + 8 * s);
                }
#pragma unroll
                for (int j = PRE; j < NST - 4; j++) {
                    mbar_expect_tx(full0 + 8 * (4 + j), STAGE);
                    bulk_load(sb + (4 + j) * STAGE, kp + j * (2 * STAGE), STAGE, full0 + 8 * (4 + j), pol);
                }
#pragma unroll
                for (int s = 0; s < NST; s++) mbar_init(empty0 + 8 * s, 8);
                mbar_init(qbar, 1);
                mbar_init(obar, 1 + 8);
                mbar_init(mlbar, 1);
                mbar_init_fence();
                mbar_expect_tx(qbar, 16 * 512);
                mbar_expect_tx(obar, 256);
                mbar_expect_tx(mlbar, 16 * 8);
                prefetch_map(&maps.wo);
                prefetch_map(&maps.v);
            }
            __syncwarp();
            cluster_arrive();
            cluster_wait();
            if (lane == 0) {
                int s = 0, ph = 0;
#pragma unroll 1
                for (int i = NST; i < 72; i++) {
                    mbar_wait_bounded(empty0 + 8 * s, ph);
                    mbar_expect_tx(full0 + 8 * s, STAGE);
                    if (i < 36) bulk_load(sb + s * STAGE, kp + (i - 4) * (2 * STAGE), STAGE, full0 + 8 * s, pol);
                    else if (i < 40) tensor_load(sb + s * STAGE, &maps.wo, rank * 256 + (i - 36) * 64, h * DH, full0 + 8 * s);
                    else tensor_load(sb + s * STAGE, &maps.v, 0, 2 * row0 + (i - 40) * 256, full0 + 8 * s, pol);
                    if (++s == NST) { s = 0; ph ^= 1; }
                }
                mbar_wait_bounded(obar, 0);
            }
        } else {
            const int grp = warp >> 2, w4 = warp & 3;
            const bool e = g & 1;
            uint32_t qf[8][2];
            {
                const __nv_bfloat16* xb = p.x + b * DM;
                const uint4 xs0 = ldg_v4(xb + lane * 16), xs1 = ldg_v4(xb + lane * 16 + 8);
                uint32_t xr[4];
#pragma unroll
                for (int i = 0; i < 4; i++) xr[i] = ldg_u16(xb + rank * 256 + (grp + (i & 2)) * 64 + w4 * 16 + (i & 1) * 8 + g);
                cluster_arrive();
                float mean_bf, sd_bf;
                ln_stats(xs0, xs1, mean_bf, sd_bf);
#pragma unroll
                for (int i = 0; i < 4; i++)
                    xr[i] = diag ? __float_as_uint(ln_apply(bf_lo(xr[i]), mean_bf, sd_bf)) >> (e ? 0 : 16) : 0u;
                float o[8][4];
#pragma unroll
                for (int j = 0; j < 8; j++) { o[j][0] = o[j][1] = o[j][2] = o[j][3] = 0.f; }
                cluster_wait();
#pragma unroll
                for (int t = 0; t < 2; t++) {
                    const int s = grp + 2 * t;
                    const uint32_t wb = sb + s * STAGE + (w4 * 16 + r + 8 * (mi >> 1)) * 256 + (mi & 1) * 128 + r * 16;
                    mbar_wait(full0 + 8 * s, 0);
                    uint32_t a[8][4];
#pragma unroll
                    for (int j = 0; j < 8; j++) ldsm4t(a[j], wb ^ (j << 4));
#pragma unroll
                    for (int j = 0; j < 8; j++) mma16816(o[j], a[j], xr[2 * t], xr[2 * t + 1]);
                    release_stage<2>(empty0 + 8 * s, lane);
                }
                float lo[16], hi[16];
#pragma unroll
                for (int j = 0; j < 8; j++) { lo[2 * j] = o[j][0]; lo[2 * j + 1] = o[j][1]; hi[2 * j] = o[j][2]; hi[2 * j + 1] = o[j][3]; }
                const float2 u0 = fold8(lo), u1 = fold8(hi);
                const uint32_t slot = sb + OFF_QPART + (rank * 8 + warp) * 512 + lane * 16;
                st_async_v4(mapa(slot, 0), u0.x, u0.y, u1.x, u1.y, mapa(qbar, 0));
                st_async_v4(mapa(slot, 1), u0.x, u0.y, u1.x, u1.y, mapa(qbar, 1));
                if (tid < 128) {
                    mbar_wait_cluster(qbar, 0);
                    float sum = 0.f;
#pragma unroll
                    for (int i = 0; i < 16; i++) sum += __uint_as_float(lds_u32(sb + OFF_QPART + i * 512 + tid * 4));
                    const int col = (tid & 2) * 32 + ((tid >> 2) & 3) * 16 + (tid & 1) * 8 + (tid >> 4);
                    sts_u16(sb + OFF_QBF + col * 2, pack_bf16(sum, 0.f));
                }
                bar_sync(1, 256);
#pragma unroll
                for (int j = 0; j < 8; j++) {
                    qf[j][0] = lds_u32(sb + OFF_QBF + ((j ^ g) * 16) + c * 4);
                    qf[j][1] = lds_u32(sb + OFF_QBF + 128 + ((j ^ g) * 16) + c * 4);
                }
            }
            {
                const uint32_t koff = (w4 * 16 + r + 8 * (mi & 1)) * 256 + (mi >> 1) * 128 + r * 16;
                uint32_t sdst = sb + OFF_S + (grp * 64 + w4 * 16 + g) * 2;
                int s = 4 + grp, ph = 0;
#pragma unroll 1
                for (int it = 0; it < 16; it++) {
                    const uint32_t kb = sb + s * STAGE + koff;
                    mbar_wait(full0 + 8 * s, ph);
                    float sa[4] = {0.f, 0.f, 0.f, 0.f}, sc[4] = {0.f, 0.f, 0.f, 0.f};
                    uint32_t a[8][4];
#pragma unroll
                    for (int j = 0; j < 8; j++) ldsm4(a[j], kb ^ (j << 4));
#pragma unroll
                    for (int j = 0; j < 8; j += 2) {
                        mma16816(sa, a[j], qf[j][0], qf[j][1]);
                        mma16816(sc, a[j + 1], qf[j + 1][0], qf[j + 1][1]);
                    }
                    release_stage<2>(empty0 + 8 * s, lane);
                    uint32_t pk = pack_bf16(e ? sa[1] + sc[1] : sa[0] + sc[0], e ? sa[3] + sc[3] : sa[2] + sc[2]);
                    pk = pack_bf16(bf_lo(pk) * 0.08838834764831845f, bf_hi(pk) * 0.08838834764831845f);
                    if (diag) { sts_u16(sdst, pk); sts_u16(sdst + 16, pk >> 16); }
                    sdst += 256;
                    s += 2;
                    if (s >= NST) { s -= NST; ph ^= 1; }
                }
            }
            {
                __syncwarp();
                const int t = (lane & 30) + grp, hf = lane & 1;
                float sv[8];
                unpack8(lds_v4(sb + OFF_S + (t * 64 + w4 * 16 + hf * 8) * 2), sv);
                float m = -3.4028234663852886e38f;
#pragma unroll
                for (int i = 0; i < 8; i++) m = fmaxf(m, sv[i]);
                m = warp_max(m);
                float l = 0.f;
#pragma unroll
                for (int i = 0; i < 8; i++) { sv[i] = exp_diff(sv[i], m); l += sv[i]; }
                l = warp_sum(l);
                if (lane < 2) st_async_v2(mapa(sb + OFF_ML + (rank * 8 + warp) * 8, lane), m, l, mapa(mlbar, lane));
                mbar_wait_cluster(mlbar, 0);
                const float2 ml = lds_f32x2(sb + OFF_ML + (lane & 15) * 8);
                const float M = warp_max(ml.x);
                float L = exp_diff(ml.x, M) * ml.y;
#pragma unroll
                for (int ofs = 8; ofs > 0; ofs >>= 1) L += __shfl_xor_sync(0xffffffffu, L, ofs);
                const float f = __fdiv_rn(exp_diff(m, M), L);
#pragma unroll
                for (int j = 0; j < 4; j++) sts_u32(sb + OFF_P + t * 128 + j * 32 + w4 * 8 + hf * 4, pack_bf16(sv[2 * j] * f, sv[2 * j + 1] * f));
            }
            uint32_t wa[8][2][4];
            {
                const int t4 = 36 + (warp >> 1), st = t4 % NST, jr = 4 * (mi >> 1) + (r >> 1);
                mbar_wait(full0 + 8 * st, (t4 / NST) & 1);
                const uint32_t wb = sb + st * STAGE + (8 * (r & 1) + jr) * 128 + ((4 * (warp & 1) + (mi & 1)) ^ jr) * 16;
#pragma unroll
                for (int t = 0; t < 8; t++)
#pragma unroll
                    for (int j = 0; j < 2; j++) ldsm4t(wa[t][j], (wb ^ (j << 5)) + t * 2048);
                release_stage<4>(empty0 + 8 * st, lane);
            }
            const uint32_t vbase = pin(sb + (8 * (mi >> 1) + r) * 256 + grp * 128 + ((2 * w4) ^ (mi & 1) ^ (r >> 2) ^ (2 * (r & 3) + grp)) * 16);
            const uint32_t o_loc = pin(sb + OFF_OPART + (warp >> 1) * 128 + rank * 64 + (g & 3) * 16 + (warp & 1) * 8 + (g >> 2) * 4);
            const uint32_t o_dst = pin(mapa(o_loc, rank ^ 1)), o_bar = pin(mapa(obar + c * 8, rank ^ 1));
            const uint32_t o_src = pin(sb + OFF_OPART + (g & 1) * 64 + c * 16), obar_p = pin(obar);
            const uint32_t first = pin((uint32_t)(c == 0));
            const bool lane0 = pin((uint32_t)(lane == 0)), odd = pin((uint32_t)(c & 1));
            unsigned long long* const acc_p = pin(p.acc + b * DM + rank * 256 + tid);
            __nv_bfloat16* const out_p = pin(p.out + b * DM + rank * 256 + warp * 32 + c * 8 + g);
            const bool feed = pin((uint32_t)((c >> 1) == (g & 1))), low = pin((uint32_t)(c < 2));
            bar_sync(1, 256);
            float oc[4][4];
#pragma unroll
            for (int j = 0; j < 4; j++) { oc[j][0] = oc[j][1] = oc[j][2] = oc[j][3] = 0.f; }
            {
                auto pv_tile = [&](uint32_t vb, const uint4& p0, const uint4& p1) {
                    uint32_t a[4][4];
#pragma unroll
                    for (int j = 0; j < 4; j++) ldsm4t(a[j], vb + j * 4096);
                    mma16816(oc[0], a[0], p0.x, p0.y);
                    mma16816(oc[1], a[1], p0.z, p0.w);
                    mma16816(oc[2], a[2], p1.x, p1.y);
                    mma16816(oc[3], a[3], p1.z, p1.w);
                };
                uint32_t psrc = sb + OFF_P + c * 32;
                uint4 pe[EG][2];
#pragma unroll
                for (int j = 0; j < EG; j++) {
                    pe[j][0] = pe[j][1] = make_uint4(0u, 0u, 0u, 0u);
                    if (feed) { pe[j][0] = lds_v4(psrc + (32 - EG + j) * 128); pe[j][1] = lds_v4(psrc + (32 - EG + j) * 128 + 16); }
                }
                int s = 40 % NST, ph = (40 / NST) & 1;
#pragma unroll 1
                for (int it = 0; it < 32 - EG; it++) {
                    uint4 p0 = make_uint4(0u, 0u, 0u, 0u), p1 = p0;
                    if (feed) { p0 = lds_v4(psrc); p1 = lds_v4(psrc + 16); }
                    psrc += 128;
                    mbar_wait(full0 + 8 * s, ph);
                    pv_tile(vbase + s * STAGE, p0, p1);
                    if (it < 32 - NST) release_stage<1>(empty0 + 8 * s, lane);
                    if (++s == NST) { s = 0; ph ^= 1; }
                }
#pragma unroll
                for (int j = 0; j < EG; j++) {
                    mbar_wait(full0 + 8 * (NST - EG + j), (72 / NST - 1) & 1);
                    pv_tile(vbase + (NST - EG + j) * STAGE, pe[j][0], pe[j][1]);
                }
            }
            const uint32_t opk = pack_bf16(
                (((oc[0][0] + oc[0][3]) + (oc[1][0] + oc[1][3])) + (oc[2][0] + oc[2][3])) + (oc[3][0] + oc[3][3]),
                (((oc[0][1] + oc[0][2]) + (oc[1][1] + oc[1][2])) + (oc[2][1] + oc[2][2])) + (oc[3][1] + oc[3][2]));
            asm volatile("{\n.reg .pred p;\nsetp.ne.u32 p, %4, 0;\n"
                         "@p st.async.shared::cluster.mbarrier::complete_tx::bytes.u32 [%0], %1, [%2];\n@p st.shared.u32 [%3], %1;\n}"
                         ::"r"(o_dst), "r"(opk), "r"(o_bar), "r"(o_loc), "r"(first) : "memory");
            __syncwarp();
            if (lane0) mbar_arrive<1>(obar_p);
            mbar_wait_cluster(obar_p, 0);
            float y0[4] = {0.f, 0.f, 0.f, 0.f}, y1[4] = {0.f, 0.f, 0.f, 0.f};
            uint4 of[4];
#pragma unroll
            for (int j = 0; j < 4; j++) of[j] = lds_v4(o_src + j * 128);
#pragma unroll
            for (int j = 0; j < 4; j++) {
                mma16816(y0, wa[2 * j][0], of[j].x, of[j].y);
                mma16816(y1, wa[2 * j][1], of[j].x, of[j].y);
                mma16816(y0, wa[2 * j + 1][0], of[j].z, of[j].w);
                mma16816(y1, wa[2 * j + 1][1], of[j].z, of[j].w);
            }
            const float z0 = odd ? y0[2] : y0[0], z1 = odd ? y0[3] : y0[1];
            const float z2 = odd ? y1[2] : y1[0], z3 = odd ? y1[3] : y1[1];
            const float asum = ((fabsf(y0[0]) + fabsf(y0[1])) + (fabsf(y0[2]) + fabsf(y0[3]))) +
                               ((fabsf(y1[0]) + fabsf(y1[1])) + (fabsf(y1[2]) + fabsf(y1[3])));
            contribute(acc_p, out_p, low ? z0 : z2, low ? z1 : z3, needs_float_path(asum));
        }
    } else {
        const int fj = cta - NATT;
        const int sh1 = fj & 1;
        const int T1 = 32 + sh1, T2 = (fj == NFFN - 1) ? (FF - (NFFN - 1) * FSL) / 16 : FSL / 16;
        uint4 xs0, xs1;
        uint32_t bias_raw[6], res_raw[6];
        if (warp < 8) {
            xs0 = ldg_v4(p.x + (warp & 1) * DM + lane * 16);
            xs1 = ldg_v4(p.x + (warp & 1) * DM + lane * 16 + 8);
#pragma unroll
            for (int j = 0; j < 6; j++) bias_raw[j] = ldg_u16(p.b1 + min(fj * FSL + (warp + 8 * (j >> 1)) * 16 + (j & 1) * 8 + g, FF - 1));
#pragma unroll
            for (int j = 0; j < 6; j++) res_raw[j] = ldg_u16((j < 4 ? p.x + (j >> 1) * DM : p.b2) + warp * 64 + c * 16 + (j & 1) * 8 + g);
        } else if (lane == 0) {
            prefetch_map(&maps.w1);
#pragma unroll
            for (int s = 0; s < NST; s++) { mbar_init(full0 + 8 * s, 1); mbar_init(empty0 + 8 * s, 8); }
            mbar_init_fence();
        }
        __syncthreads();
        if (warp == 8) {
            if (lane == 0) {
                const char* p2 = (const char*)(p.w2 + (size_t)fj * FSL * DM);
                const uint64_t pol = policy_evict_first();
                int s = 0, ph = 1;
#pragma unroll 1
                for (int i = 0; i < T1 + T2 + NST; i++) {
                    mbar_wait_bounded(empty0 + 8 * s, ph);
                    if (i < T1) {
                        mbar_expect_tx(full0 + 8 * s, 16 * FSL * 2);
                        tensor_load(sb + s * STAGE, &maps.w1, fj * (FSL / 2), i * 16 - sh1, full0 + 8 * s, pol);
                    } else if (i < T1 + T2) {
                        mbar_expect_tx(full0 + 8 * s, STAGE);
                        bulk_load(sb + s * STAGE, p2 + (size_t)(i - T1) * STAGE, STAGE, full0 + 8 * s, pol);
                    }
                    if (++s == NST) { s = 0; ph ^= 1; }
                }
            }
        } else {
            const uint32_t xn_s = sb + OFF_QPART;
            const uint32_t g_s = xn_s + 2 * 1056;
            if (warp < 2) {
                float mean_bf, sd_bf, xn[16];
                ln_stats(xs0, xs1, mean_bf, sd_bf);
                unpack8(xs0, xn); unpack8(xs1, xn + 8);
#pragma unroll
                for (int i = 0; i < 16; i++) sts_u16(xn_s + warp * 1056 + (lane * 16 + i + sh1) * 2, pack_bf16(ln_apply(xn[i], mean_bf, sd_bf), 0.f));
                if (lane < 16) sts_u16(xn_s + warp * 1056 + (lane == 15 && sh1 ? 0 : DM + sh1 + lane) * 2, 0);
            }
            bar_sync(1, 256);
            int s = 0, ph = 0;
            float hacc[3][4];
#pragma unroll
            for (int j = 0; j < 3; j++) { hacc[j][0] = hacc[j][1] = hacc[j][2] = hacc[j][3] = 0.f; }
            uint32_t aoff[3];
#pragma unroll
            for (int j = 0; j < 3; j++) aoff[j] = (r + 8 * (mi >> 1)) * (FSL * 2) + min(2 * (warp + 8 * j) + (mi & 1), FSL / 8 - 1) * 16;
#pragma unroll 1
            for (int i = 0; i < T1; i++) {
                uint32_t f0 = 0, f1 = 0;
                if (g < 2) { f0 = lds_u32(xn_s + g * 1056 + i * 32 + c * 4); f1 = lds_u32(xn_s + g * 1056 + i * 32 + 16 + c * 4); }
                mbar_wait(full0 + 8 * s, ph);
#pragma unroll
                for (int j = 0; j < 3; j++) {
                    uint32_t a[4];
                    ldsm4t(a, sb + s * STAGE + aoff[j]);
                    mma16816(hacc[j], a, f0, f1);
                }
                release_stage<1>(empty0 + 8 * s, lane);
                if (++s == NST) { s = 0; ph ^= 1; }
            }
            if (c == 0) {
#pragma unroll
                for (int j = 0; j < 3; j++)
#pragma unroll
                    for (int hf = 0; hf < 2; hf++) {
                        const int f = (warp + 8 * j) * 16 + hf * 8 + g;
                        if (f < FSL) {
                            const float bias = bf_lo(bias_raw[2 * j + hf]);
#pragma unroll
                            for (int bb = 0; bb < 2; bb++) {
                                const float hv = rbf(rbf(hacc[j][2 * hf + bb]) + bias);
                                const float inner = 0.7978845608028654f * (hv + 0.044715f * hv * hv * hv);
                                sts_u16(g_s + bb * 704 + f * 2, pack_bf16(0.5f * hv * (1.f + tanhf(inner)), 0.f));
                            }
                        }
                    }
            }
            bar_sync(1, 256);
            float y[2][4][4];
#pragma unroll
            for (int bb = 0; bb < 2; bb++)
#pragma unroll
                for (int j = 0; j < 4; j++) { y[bb][j][0] = y[bb][j][1] = y[bb][j][2] = y[bb][j][3] = 0.f; }
            const int sh = (g & 1) * 16;
#pragma unroll 1
            for (int i = 0; i < T2; i++) {
                uint32_t f[2][2] = {{0u, 0u}, {0u, 0u}};
                if (diag) {
#pragma unroll
                    for (int bb = 0; bb < 2; bb++) {
                        f[bb][0] = lds_u16(g_s + bb * 704 + (i * 16 + g) * 2) << sh;
                        f[bb][1] = lds_u16(g_s + bb * 704 + (i * 16 + 8 + g) * 2) << sh;
                    }
                }
                const uint32_t wb = sb + s * STAGE + (r + 8 * (mi >> 1)) * 1024 + warp * 128 + (((mi & 1) * 4) ^ r) * 16;
                mbar_wait(full0 + 8 * s, ph);
#pragma unroll
                for (int j = 0; j < 4; j++) {
                    uint32_t a[4];
                    ldsm4t(a, wb ^ (j << 4));
                    mma16816(y[0][j], a, f[0][0], f[0][1]);
                    mma16816(y[1][j], a, f[1][0], f[1][1]);
                }
                release_stage<1>(empty0 + 8 * s, lane);
                if (++s == NST) { s = 0; ph ^= 1; }
            }
#pragma unroll
            for (int bb = 0; bb < 2; bb++) {
                float yy[16];
#pragma unroll
                for (int j = 0; j < 4; j++) { yy[2 * j] = y[bb][j][0]; yy[2 * j + 1] = y[bb][j][1]; yy[8 + 2 * j] = y[bb][j][2]; yy[8 + 2 * j + 1] = y[bb][j][3]; }
                float2 yo = fold8(yy);
                if (fj == 0) {
                    yo.x += bf_lo(res_raw[2 * bb]) + bf_lo(res_raw[4]);
                    yo.y += bf_lo(res_raw[2 * bb + 1]) + bf_lo(res_raw[5]);
                }
                const int n0 = bb * DM + warp * 64 + c * 16;
                unsigned long long* a = p.acc + (n0 & ~31) + 4 * g + 2 * (c & 1);
                const bool fp = needs_float_path(warp_max(fabsf(yo.x) + fabsf(yo.y)));
                contribute(a, p.out + n0 + g, yo.x, 0.f, fp);
                contribute(a + 1, p.out + n0 + 8 + g, yo.y, 0.f, fp);
            }
        }
    }
}

typedef CUresult (*EncodeFn)(CUtensorMap*, CUtensorMapDataType, cuuint32_t, void*, const cuuint64_t*, const cuuint64_t*,
                             const cuuint32_t*, const cuuint32_t*, CUtensorMapInterleave, CUtensorMapSwizzle,
                             CUtensorMapL2promotion, CUtensorMapFloatOOBfill);

void encode_2d(EncodeFn fn, CUtensorMap* map, CUtensorMapDataType dt, const void* base, uint64_t cols, uint64_t rows,
               uint64_t pitch_bytes, uint32_t box_cols, uint32_t box_rows, CUtensorMapSwizzle sw) {
    const cuuint64_t dims[2] = {cols, rows}, strides[1] = {pitch_bytes};
    const cuuint32_t box[2] = {box_cols, box_rows}, estr[2] = {1, 1};
    fn(map, dt, 2, const_cast<void*>(base), dims, strides, box, estr, CU_TENSOR_MAP_INTERLEAVE_NONE, sw,
       CU_TENSOR_MAP_L2_PROMOTION_NONE, CU_TENSOR_MAP_FLOAT_OOB_FILL_NONE);
}

}

extern "C" void kernel_launch(void* const* d_in, const int* in_sizes, int n_in, void* d_out, int out_size) {
    (void)in_sizes; (void)n_in; (void)out_size;
    typedef const __nv_bfloat16* P;
    static EncodeFn encode = nullptr;
    static void* acc = nullptr;
    if (!encode) {
        cudaFuncSetAttribute(fused_decode_kernel, cudaFuncAttributeMaxDynamicSharedMemorySize, SMEM_BYTES);
        cudaDriverEntryPointQueryResult st;
        cudaGetDriverEntryPoint("cuTensorMapEncodeTiled", (void**)&encode, cudaEnableDefault, &st);
        cudaGetSymbolAddress(&acc, g_acc);
    }
    Params p;
    p.kc = (P)d_in[1]; p.x = (P)d_in[0];
    p.acc = (unsigned long long*)acc; p.out = (__nv_bfloat16*)d_out;
    p.w2 = (P)d_in[8]; p.b1 = (P)d_in[7]; p.b2 = (P)d_in[9];
    Maps maps;
    encode_2d(encode, &maps.wq, CU_TENSOR_MAP_DATA_TYPE_BFLOAT16, d_in[3], NH * DH, DM, NH * DH * 2, DH, 64,
              CU_TENSOR_MAP_SWIZZLE_NONE);
    encode_2d(encode, &maps.v, CU_TENSOR_MAP_DATA_TYPE_BFLOAT16, d_in[2], 64, (uint64_t)2 * 2 * NH * SK, 128, 64, 128,
              CU_TENSOR_MAP_SWIZZLE_128B);
    encode_2d(encode, &maps.wo, CU_TENSOR_MAP_DATA_TYPE_BFLOAT16, d_in[4], DM, NH * DH, DM * 2, 64, 128,
              CU_TENSOR_MAP_SWIZZLE_128B);
    encode_2d(encode, &maps.w1, CU_TENSOR_MAP_DATA_TYPE_UINT32, d_in[6], FF / 2, DM, FF * 2, FSL / 2, 16,
              CU_TENSOR_MAP_SWIZZLE_NONE);
    fused_decode_kernel<<<NCTA, NTHREADS, SMEM_BYTES>>>(p, maps);
}
```

```cpp
#include <cuda.h>
#include <cuda_runtime.h>
#include <cuda_bf16.h>
#include <stdint.h>

namespace {

constexpr int DM = 512, NH = 32, SK = 16384, WIN = 4096, DH = 128, FF = 1376;
constexpr int NATT = 128, NFFN = 4, NCTA = NATT + NFFN;
constexpr int NPROD = NH + NFFN;
constexpr int FSL = 352;
constexpr int NST = 8;
constexpr int STAGE = 16384;
constexpr int PRE = 2;
constexpr int EG = 4;
constexpr int NTHREADS = 288;
static_assert(NST % 2 == 0 && 72 % NST == 0 && EG + 4 <= NST, "ring geometry");

constexpr int OFF_QPART = NST * STAGE;
constexpr int OFF_S = OFF_QPART, OFF_P = OFF_QPART + 4096;
constexpr int OFF_OPART = OFF_QPART + 8192;
constexpr int OFF_ML = OFF_OPART + 1024;
constexpr int OFF_QBF = OFF_ML + 128;
constexpr int OFF_BAR = OFF_QBF + 256;
constexpr int SMEM_BYTES = OFF_BAR + (2 * NST + 3) * 8;

__device__ __align__(256) unsigned long long g_acc[2 * 2 * DM];

struct Params {
    const __nv_bfloat16 *kc, *x;
    unsigned long long* acc;
    __nv_bfloat16* out;
    const __nv_bfloat16 *w2, *b1, *b2;
    int t_end, t_kv, t_wo, t_stag;
};
struct Maps {
    alignas(64) CUtensorMap wq, v, wo, w1;
};

__device__ __forceinline__ void mbar_init(uint32_t bar, uint32_t cnt) {
    asm volatile("mbarrier.init.shared::cta.b64 [%0], %1;" ::"r"(bar), "r"(cnt) : "memory");
}
__device__ __forceinline__ void mbar_init_fence() { asm volatile("fence.mbarrier_init.release.cluster;" ::: "memory"); }
__device__ __forceinline__ void mbar_expect_tx(uint32_t bar, uint32_t bytes) {
    asm volatile("mbarrier.arrive.expect_tx.shared::cta.b64 _, [%0], %1;" ::"r"(bar), "r"(bytes) : "memory");
}
template <int N>
__device__ __forceinline__ void mbar_arrive(uint32_t bar) {
    asm volatile("mbarrier.arrive.shared::cta.b64 _, [%0], %1;" ::"r"(bar), "n"(N) : "memory");
}
template <int N>
__device__ __forceinline__ void release_stage(uint32_t bar, int lane) {
    asm volatile("fence.proxy.async.shared::cta;" ::: "memory");
    __syncwarp();
    if (lane == 0) mbar_arrive<N>(bar);
}
#define WAIT_LIMIT (1u << 18)
__device__ __forceinline__ void mbar_wait_bounded(uint32_t bar, uint32_t parity) {
    uint32_t ok, n = 0;
    do {
        if (++n > WAIT_LIMIT) __trap();
        asm volatile(
            "{\n.reg .pred p;\nmbarrier.try_wait.parity.shared::cta.b64 p, [%1], %2;\nselp.u32 %0, 1, 0, p;\n}\n"
            : "=r"(ok) : "r"(bar), "r"(parity) : "memory");
    } while (!ok);
}
__device__ __forceinline__ void mbar_wait(uint32_t bar, uint32_t parity) {
    asm volatile(
        "{\n.reg .pred p;\nWAIT_LOOP:\nmbarrier.try_wait.parity.shared::cta.b64 p, [%0], %1;\n@!p bra WAIT_LOOP;\n}\n"
        ::"r"(bar), "r"(parity) : "memory");
}
__device__ __forceinline__ void mbar_wait_cluster(uint32_t bar, uint32_t parity) {
    asm volatile(
        "{\n.reg .pred p;\nWAIT_LOOP:\nmbarrier.try_wait.parity.acquire.cluster.shared::cta.b64 p, [%0], %1;\n@!p bra WAIT_LOOP;\n}\n"
        ::"r"(bar), "r"(parity) : "memory");
}
__device__ __forceinline__ uint64_t policy_evict_first() {
    uint64_t pol;
    asm volatile("createpolicy.fractional.L2::evict_first.b64 %0, 1.0;" : "=l"(pol));
    return pol;
}
__device__ __forceinline__ void bulk_load(uint32_t dst, const void* src, uint32_t bytes, uint32_t bar, uint64_t pol) {
    asm volatile("cp.async.bulk.shared::cluster.global.mbarrier::complete_tx::bytes.L2::cache_hint [%0], [%1], %2, [%3], %4;"
                 ::"r"(dst), "l"(src), "r"(bytes), "r"(bar), "l"(pol) : "memory");
}
__device__ __forceinline__ void tensor_load(uint32_t dst, const CUtensorMap* map, int cx, int cy, uint32_t bar) {
    asm volatile("cp.async.bulk.tensor.2d.shared::cluster.global.mbarrier::complete_tx::bytes [%0], [%1, {%2, %3}], [%4];"
                 ::"r"(dst), "l"(map), "r"(cx), "r"(cy), "r"(bar) : "memory");
}
__device__ __forceinline__ void tensor_load(uint32_t dst, const CUtensorMap* map, int cx, int cy, uint32_t bar, uint64_t pol) {
    asm volatile("cp.async.bulk.tensor.2d.shared::cluster.global.mbarrier::complete_tx::bytes.L2::cache_hint [%0], [%1, {%2, %3}], [%4], %5;"
                 ::"r"(dst), "l"(map), "r"(cx), "r"(cy), "r"(bar), "l"(pol) : "memory");
}
__device__ __forceinline__ void tensor_load3(uint32_t dst, const CUtensorMap* map, int cx, int cy, int cz, uint32_t bar) {
    asm volatile("cp.async.bulk.tensor.3d.shared::cluster.global.mbarrier::complete_tx::bytes [%0], [%1, {%2, %3, %4}], [%5];"
                 ::"r"(dst), "l"(map), "r"(cx), "r"(cy), "r"(cz), "r"(bar) : "memory");
}
__device__ __forceinline__ void prefetch_map(const CUtensorMap* map) {
    asm volatile("prefetch.tensormap [%0];" ::"l"(map) : "memory");
}
__device__ __forceinline__ uint4 ldg_v4(const void* p) {
    uint4 v;
    asm volatile("ld.global.v4.u32 {%0,%1,%2,%3}, [%4];" : "=r"(v.x), "=r"(v.y), "=r"(v.z), "=r"(v.w) : "l"(p) : "memory");
    return v;
}
__device__ __forceinline__ uint32_t ldg_u16(const void* p) {
    uint16_t v;
    asm volatile("ld.global.u16 %0, [%1];" : "=h"(v) : "l"(p) : "memory");
    return v;
}
__device__ __forceinline__ void ldsm4(uint32_t (&r)[4], uint32_t addr) {
    asm volatile("ldmatrix.sync.aligned.m8n8.x4.shared.b16 {%0,%1,%2,%3}, [%4];"
                 : "=r"(r[0]), "=r"(r[1]), "=r"(r[2]), "=r"(r[3]) : "r"(addr) : "memory");
}
__device__ __forceinline__ void ldsm4t(uint32_t (&r)[4], uint32_t addr) {
    asm volatile("ldmatrix.sync.aligned.m8n8.x4.trans.shared.b16 {%0,%1,%2,%3}, [%4];"
                 : "=r"(r[0]), "=r"(r[1]), "=r"(r[2]), "=r"(r[3]) : "r"(addr) : "memory");
}
__device__ __forceinline__ void mma16816(float (&d)[4], const uint32_t (&a)[4], uint32_t b0, uint32_t b1) {
    asm volatile(
        "mma.sync.aligned.m16n8k16.row.col.f32.bf16.bf16.f32 {%0,%1,%2,%3}, {%4,%5,%6,%7}, {%8,%9}, {%0,%1,%2,%3};"
        : "+f"(d[0]), "+f"(d[1]), "+f"(d[2]), "+f"(d[3])
        : "r"(a[0]), "r"(a[1]), "r"(a[2]), "r"(a[3]), "r"(b0), "r"(b1));
}
__device__ __forceinline__ uint32_t mapa(uint32_t addr, uint32_t rank) {
    uint32_t r;
    asm("mapa.shared::cluster.u32 %0, %1, %2;" : "=r"(r) : "r"(addr), "r"(rank));
    return r;
}
__device__ __forceinline__ void st_async_v4(uint32_t addr, float a, float b, float c, float d, uint32_t bar) {
    asm volatile("st.async.shared::cluster.mbarrier::complete_tx::bytes.v4.f32 [%0], {%1,%2,%3,%4}, [%5];"
                 ::"r"(addr), "f"(a), "f"(b), "f"(c), "f"(d), "r"(bar) : "memory");
}
__device__ __forceinline__ void st_async_v2(uint32_t addr, float a, float b, uint32_t bar) {
    asm volatile("st.async.shared::cluster.mbarrier::complete_tx::bytes.v2.f32 [%0], {%1,%2}, [%3];"
                 ::"r"(addr), "f"(a), "f"(b), "r"(bar) : "memory");
}
__device__ __forceinline__ uint32_t lds_u16(uint32_t addr) {
    uint16_t v;
    asm volatile("ld.shared.u16 %0, [%1];" : "=h"(v) : "r"(addr) : "memory");
    return v;
}
__device__ __forceinline__ uint32_t lds_u32(uint32_t addr) {
    uint32_t v;
    asm volatile("ld.shared.u32 %0, [%1];" : "=r"(v) : "r"(addr) : "memory");
    return v;
}
__device__ __forceinline__ float2 lds_f32x2(uint32_t addr) {
    float2 v;
    asm volatile("ld.shared.v2.f32 {%0,%1}, [%2];" : "=f"(v.x), "=f"(v.y) : "r"(addr) : "memory");
    return v;
}
__device__ __forceinline__ uint4 lds_v4(uint32_t addr) {
    uint4 v;
    asm volatile("ld.shared.v4.u32 {%0,%1,%2,%3}, [%4];" : "=r"(v.x), "=r"(v.y), "=r"(v.z), "=r"(v.w) : "r"(addr) : "memory");
    return v;
}
__device__ __forceinline__ void sts_u16(uint32_t addr, uint32_t v) {
    asm volatile("st.shared.u16 [%0], %1;" ::"r"(addr), "h"((uint16_t)v) : "memory");
}
__device__ __forceinline__ void sts_u32(uint32_t addr, uint32_t v) {
    asm volatile("st.shared.u32 [%0], %1;" ::"r"(addr), "r"(v) : "memory");
}
__device__ __forceinline__ void bar_sync(int id, int n) { asm volatile("bar.sync %0, %1;" ::"r"(id), "r"(n) : "memory"); }
__device__ __forceinline__ void cluster_arrive() { asm volatile("barrier.cluster.arrive.relaxed.aligned;" ::: "memory"); }
__device__ __forceinline__ void cluster_wait() { asm volatile("barrier.cluster.wait.acquire.aligned;" ::: "memory"); }

__device__ __forceinline__ uint32_t now_ns() {
    uint32_t t;
    asm volatile("mov.u32 %0, %%globaltimer_lo;" : "=r"(t));
    return t;
}
__device__ __forceinline__ uint32_t pin(uint32_t v) { return __shfl_sync(0xffffffffu, v, threadIdx.x & 31); }
template <class T>
__device__ __forceinline__ T* pin(T* q) {
    const uint64_t v = (uint64_t)q;
    return (T*)(((uint64_t)pin((uint32_t)(v >> 32)) << 32) | pin((uint32_t)v));
}

__device__ __forceinline__ uint32_t pack_bf16(float lo, float hi) {
    uint32_t r;
    asm("cvt.rn.bf16x2.f32 %0, %1, %2;" : "=r"(r) : "f"(hi), "f"(lo));
    return r;
}
__device__ __forceinline__ float bf_lo(uint32_t v) { return __uint_as_float(v << 16); }
__device__ __forceinline__ float bf_hi(uint32_t v) { return __uint_as_float(v & 0xffff0000u); }
__device__ __forceinline__ float rbf(float x) { return bf_lo(pack_bf16(x, 0.f)); }
__device__ __forceinline__ float exp_diff(float a, float b) {
    float r;
    asm("ex2.approx.ftz.f32 %0, %1;" : "=f"(r) : "f"((a - b) * 1.4426950408889634f));
    return r;
}
__device__ __forceinline__ float warp_max(float x) {
    int k = __float_as_int(x);
    k ^= (k >> 31) & 0x7fffffff;
    k = __reduce_max_sync(0xffffffffu, k);
    k ^= (k >> 31) & 0x7fffffff;
    return __int_as_float(k);
}
__device__ __forceinline__ float warp_sum(float x) {
#pragma unroll
    for (int o = 16; o > 0; o >>= 1) x += __shfl_xor_sync(0xffffffffu, x, o);
    return x;
}
__device__ __forceinline__ void unpack8(const uint4& v, float* f) {
    f[0] = bf_lo(v.x); f[1] = bf_hi(v.x); f[2] = bf_lo(v.y); f[3] = bf_hi(v.y);
    f[4] = bf_lo(v.z); f[5] = bf_hi(v.z); f[6] = bf_lo(v.w); f[7] = bf_hi(v.w);
}
__device__ __forceinline__ void ln_stats(const uint4& a, const uint4& b, float& mean_bf, float& sd_bf) {
    float f[16];
    unpack8(a, f); unpack8(b, f + 8);
    float s = 0.f;
#pragma unroll
    for (int i = 0; i < 16; i++) s += f[i];
    const float mean = warp_sum(s) * (1.f / DM);
    float q = 0.f;
#pragma unroll
    for (int i = 0; i < 16; i++) { const float d = f[i] - mean; q = fmaf(d, d, q); }
    const float var = warp_sum(q) * (1.f / DM);
    mean_bf = rbf(mean);
    sd_bf = rbf(__fsqrt_rn(rbf(rbf(var) + 1e-5f)));
}
__device__ __forceinline__ float ln_apply(float x, float mean_bf, float sd_bf) {
    return rbf(__fdiv_rn(rbf(x - mean_bf), sd_bf));
}
__device__ __forceinline__ float2 fold8(const float* c) {
    float v[8];
#pragma unroll
    for (int i = 0; i < 8; i++) v[i] = c[2 * i] + c[2 * (i ^ 1) + 1];
    const float w0 = v[0] + __shfl_xor_sync(0xffffffffu, v[2], 1);
    const float w1 = v[1] + __shfl_xor_sync(0xffffffffu, v[3], 1);
    const float w4 = v[4] + __shfl_xor_sync(0xffffffffu, v[6], 1);
    const float w5 = v[5] + __shfl_xor_sync(0xffffffffu, v[7], 1);
    return make_float2(w0 + __shfl_xor_sync(0xffffffffu, w4, 2), w1 + __shfl_xor_sync(0xffffffffu, w5, 2));
}

__device__ __forceinline__ bool needs_float_path(float mag) {
    return !(mag < 0x1p13f) || mag < 0x1p-12f;
}
__device__ __forceinline__ bool add_fixed(unsigned long long* a, __nv_bfloat16* o, long long v, bool skip, float& sum) {
    uint32_t lo = (uint32_t)v, hi = (uint32_t)(v >> 32) + 0x1000000u;
    asm volatile("{\n.reg .pred p;\n.reg .b64 t;\nsetp.eq.u32 p, %3, 0;\nmov.b64 t, {%0, %1};\n"
                 "@p atom.relaxed.gpu.global.add.u64 t, [%2], t;\nmov.b64 {%0, %1}, t;\n}"
                 : "+r"(lo), "+r"(hi) : "l"(a), "r"((uint32_t)skip) : "memory");
    const unsigned long long r = (((unsigned long long)hi << 32) | lo) + ((unsigned long long)v + (1ull << 31) - ((unsigned long long)(NPROD - 1) << 56));
    const uint32_t t = (uint32_t)(r >> 32) + 0x800000u;
    const float frac = (float)(int)((uint32_t)r ^ 0x80000000u) * 0x1p-36f;
    const uint32_t pk = pack_bf16(fmaf((float)(int)(r >> 32), 0x1p-4f, frac), 0.f);
    asm volatile("{\n.reg .pred p, q;\nsetp.eq.u32 q, %4, 0;\nsetp.lt.and.u32 p, %3, 0x1000000, q;\n"
                 "@p st.global.u16 [%0], %1;\n@p st.global.u64 [%2], 0;\n}"
                 ::"l"(o), "h"((uint16_t)pk), "l"(a), "r"(t), "r"((uint32_t)skip) : "memory");
    sum = fmaf((float)(int)((uint32_t)(r >> 32) ^ 0x80000000u), 0x1p-4f, frac);
    return (t ^ 0x80000000u) < 0x1000000u;
}
__device__ __noinline__ void finish_flagged(unsigned long long* a, __nv_bfloat16* o, float sum) {
    float side;
    asm volatile("fence.acq_rel.gpu;" ::: "memory");
    asm volatile("atom.relaxed.gpu.global.exch.b32 %0, [%1+8192], 0;" : "=f"(side) : "l"(a) : "memory");
    asm volatile("st.global.u16 [%0], %1;" ::"l"(o), "h"((uint16_t)pack_bf16(sum + side, 0.f)) : "memory");
    asm volatile("st.global.u64 [%0], %1;" ::"l"(a), "l"(0ull) : "memory");
}
__device__ __noinline__ void add_float(unsigned long long* a, __nv_bfloat16* o, float y) {
    asm volatile("red.relaxed.gpu.global.add.f32 [%0+8192], %1;" ::"l"(a), "f"(y) : "memory");
    asm volatile("red.release.gpu.global.or.b64 [%0], %1;" ::"l"(a), "l"(1ull << 63) : "memory");
    float sum;
    if (add_fixed(a, o, 0, false, sum)) finish_flagged(a, o, sum);
}
__device__ __forceinline__ void contribute(unsigned long long* a, __nv_bfloat16* o, float y, bool float_path) {
    float sum;
    const bool flagged = add_fixed(a, o, __float2ll_rn(y * 0x1p36f), float_path, sum);
    if (__builtin_expect(float_path, 0)) add_float(a, o, y);
    else if (__builtin_expect(flagged, 0)) finish_flagged(a, o, sum);
}

__global__ void __cluster_dims__(2, 1, 1) __launch_bounds__(NTHREADS, 1)
fused_decode_kernel(const __grid_constant__ Params p, const __grid_constant__ Maps maps) {
    extern __shared__ __align__(1024) unsigned char smem[];
    if (threadIdx.x == 0 && blockIdx.x < NATT) {
        const uint32_t ct = blockIdx.x;
        const char* k0 = (const char*)p.kc + (size_t)((((ct >> 1) & 1) * NH + (ct >> 2)) * SK + (SK - WIN) + (ct & 1) * 64) * (DH * 2);
        asm volatile("cp.async.bulk.prefetch.L2.global.L2::cache_hint [%0], %1, %2;"
                     ::"l"(k0), "r"(STAGE), "l"(policy_evict_first()) : "memory");
    }
    const uint32_t sb = (uint32_t)__cvta_generic_to_shared(smem);
    const uint32_t full0 = sb + OFF_BAR, empty0 = full0 + NST * 8;
    const uint32_t qbar = empty0 + NST * 8, obar = qbar + 8, mlbar = obar + 8;
    const int tid = threadIdx.x, warp = tid >> 5, lane = tid & 31;
    const int cta = blockIdx.x;
    const int g = lane >> 2, c = lane & 3;
    const int r = lane & 7, mi = lane >> 3;
    const bool diag = (c == (g >> 1));

    if (cta < NATT) {
        const int rank = cta & 1, b = (cta >> 1) & 1, h = cta >> 2;
        if (warp == 8) {
            const int row0 = (b * NH + h) * SK + (SK - WIN) + rank * 64;
            const char* kp = (const char*)(p.kc + (size_t)row0 * DH);
            const uint64_t pol = policy_evict_first();
            uint32_t due = 0;
            if (lane == 0) {
#pragma unroll
                for (int s = 0; s < NST; s++) mbar_init(full0 + 8 * s, 1);
                mbar_init_fence();
#pragma unroll
                for (int j = 0; j < PRE; j++) {
                    mbar_expect_tx(full0 + 8 * (4 + j), STAGE);
                    bulk_load(sb + (4 + j) * STAGE, kp + j * (2 * STAGE), STAGE, full0 + 8 * (4 + j), pol);
                }
#pragma unroll
                for (int s = 0; s < 4; s++) {
                    mbar_expect_tx(full0 + 8 * s, STAGE);
                    tensor_load(sb + s * STAGE, &maps.wq, h * DH, rank * 256 + s * 64, full0 + 8 * s);
                }
#pragma unroll
                for (int j = PRE; j < NST - 4; j++) {
                    mbar_expect_tx(full0 + 8 * (4 + j), STAGE);
                    bulk_load(sb + (4 + j) * STAGE, kp + j * (2 * STAGE), STAGE, full0 + 8 * (4 + j), pol);
                }
#pragma unroll
                for (int s = 0; s < NST; s++) mbar_init(empty0 + 8 * s, 8);
                mbar_init(qbar, 1);
                mbar_init(obar, 1 + 8);
                mbar_init(mlbar, 1);
                mbar_init_fence();
                mbar_expect_tx(qbar, 16 * 512);
                mbar_expect_tx(obar, 512);
                mbar_expect_tx(mlbar, 16 * 8);
                due = now_ns() + p.t_end - ((h * p.t_stag) >> 5) - 4 * p.t_wo - (67 - NST) * p.t_kv;
                prefetch_map(&maps.v);
                prefetch_map(&maps.wo);
            }
            __syncwarp();
            cluster_arrive();
            cluster_wait();
            if (lane == 0) {
                int s = 0, ph = 0;
#pragma unroll 1
                for (int i = NST; i < 72; i++) {
                    mbar_wait_bounded(empty0 + 8 * s, ph);
                    mbar_expect_tx(full0 + 8 * s, STAGE);
                    for (uint32_t n = 0; (int)(now_ns() - due) < 0 && n < WAIT_LIMIT; n++) {}
                    if (i < 36) bulk_load(sb + s * STAGE, kp + (i - 4) * (2 * STAGE), STAGE, full0 + 8 * s, pol);
                    else if (i < 68) tensor_load(sb + s * STAGE, &maps.v, 0, 2 * row0 + (i - 36) * 256, full0 + 8 * s, pol);
                    else tensor_load3(sb + s * STAGE, &maps.wo, 0, h * DH + (i - 68) * 32, rank * 4, full0 + 8 * s);
                    due += i < 67 ? p.t_kv : p.t_wo;
                    if (++s == NST) { s = 0; ph ^= 1; }
                }
                mbar_wait_bounded(obar, 0);
#pragma unroll 1
                for (int t = NST - 4; t < NST; t++) mbar_wait_bounded(full0 + 8 * t, (72 / NST - 1) & 1);
            }
        } else {
            const int grp = warp >> 2, w4 = warp & 3;
            const bool e = g & 1;
            uint32_t qf[8][2];
            {
                const __nv_bfloat16* xb = p.x + b * DM;
                const uint4 xs0 = ldg_v4(xb + lane * 16), xs1 = ldg_v4(xb + lane * 16 + 8);
                uint32_t xr[4];
#pragma unroll
                for (int i = 0; i < 4; i++) xr[i] = ldg_u16(xb + rank * 256 + (grp + (i & 2)) * 64 + w4 * 16 + (i & 1) * 8 + g);
                cluster_arrive();
                float mean_bf, sd_bf;
                ln_stats(xs0, xs1, mean_bf, sd_bf);
#pragma unroll
                for (int i = 0; i < 4; i++)
                    xr[i] = diag ? __float_as_uint(ln_apply(bf_lo(xr[i]), mean_bf, sd_bf)) >> (e ? 0 : 16) : 0u;
                float o[8][4];
#pragma unroll
                for (int j = 0; j < 8; j++) { o[j][0] = o[j][1] = o[j][2] = o[j][3] = 0.f; }
                cluster_wait();
#pragma unroll
                for (int t = 0; t < 2; t++) {
                    const int s = grp + 2 * t;
                    const uint32_t wb = sb + s * STAGE + (w4 * 16 + r + 8 * (mi >> 1)) * 256 + (mi & 1) * 128 + r * 16;
                    mbar_wait(full0 + 8 * s, 0);
                    uint32_t a[8][4];
#pragma unroll
                    for (int j = 0; j < 8; j++) ldsm4t(a[j], wb ^ (j << 4));
#pragma unroll
                    for (int j = 0; j < 8; j++) mma16816(o[j], a[j], xr[2 * t], xr[2 * t + 1]);
                    release_stage<2>(empty0 + 8 * s, lane);
                }
                float lo[16], hi[16];
#pragma unroll
                for (int j = 0; j < 8; j++) { lo[2 * j] = o[j][0]; lo[2 * j + 1] = o[j][1]; hi[2 * j] = o[j][2]; hi[2 * j + 1] = o[j][3]; }
                const float2 u0 = fold8(lo), u1 = fold8(hi);
                const uint32_t slot = sb + OFF_QPART + (rank * 8 + warp) * 512 + lane * 16;
                st_async_v4(mapa(slot, 0), u0.x, u0.y, u1.x, u1.y, mapa(qbar, 0));
                st_async_v4(mapa(slot, 1), u0.x, u0.y, u1.x, u1.y, mapa(qbar, 1));
                if (tid < 128) {
                    mbar_wait_cluster(qbar, 0);
                    float sum = 0.f;
#pragma unroll
                    for (int i = 0; i < 16; i++) sum += __uint_as_float(lds_u32(sb + OFF_QPART + i * 512 + tid * 4));
                    const int col = (tid & 2) * 32 + ((tid >> 2) & 3) * 16 + (tid & 1) * 8 + (tid >> 4);
                    sts_u16(sb + OFF_QBF + col * 2, pack_bf16(sum, 0.f));
                }
                bar_sync(1, 256);
#pragma unroll
                for (int j = 0; j < 8; j++) {
                    qf[j][0] = lds_u32(sb + OFF_QBF + ((j ^ g) * 16) + c * 4);
                    qf[j][1] = lds_u32(sb + OFF_QBF + 128 + ((j ^ g) * 16) + c * 4);
                }
            }
            {
                const uint32_t koff = (w4 * 16 + r + 8 * (mi & 1)) * 256 + (mi >> 1) * 128 + r * 16;
                uint32_t sdst = sb + OFF_S + (grp * 64 + w4 * 16 + g) * 2;
                int s = 4 + grp, ph = 0;
#pragma unroll 1
                for (int it = 0; it < 16; it++) {
                    const uint32_t kb = sb + s * STAGE + koff;
                    mbar_wait(full0 + 8 * s, ph);
                    float sa[4] = {0.f, 0.f, 0.f, 0.f}, sc[4] = {0.f, 0.f, 0.f, 0.f};
                    uint32_t a[8][4];
#pragma unroll
                    for (int j = 0; j < 8; j++) ldsm4(a[j], kb ^ (j << 4));
#pragma unroll
                    for (int j = 0; j < 8; j += 2) {
                        mma16816(sa, a[j], qf[j][0], qf[j][1]);
                        mma16816(sc, a[j + 1], qf[j + 1][0], qf[j + 1][1]);
                    }
                    release_stage<2>(empty0 + 8 * s, lane);
                    uint32_t pk = pack_bf16(e ? sa[1] + sc[1] : sa[0] + sc[0], e ? sa[3] + sc[3] : sa[2] + sc[2]);
                    pk = pack_bf16(bf_lo(pk) * 0.08838834764831845f, bf_hi(pk) * 0.08838834764831845f);
                    if (diag) { sts_u16(sdst, pk); sts_u16(sdst + 16, pk >> 16); }
                    sdst += 256;
                    s += 2;
                    if (s >= NST) { s -= NST; ph ^= 1; }
                }
            }
            {
                __syncwarp();
                const int t = (lane & 30) + grp, hf = lane & 1;
                float sv[8];
                unpack8(lds_v4(sb + OFF_S + (t * 64 + w4 * 16 + hf * 8) * 2), sv);
                float m = -3.4028234663852886e38f;
#pragma unroll
                for (int i = 0; i < 8; i++) m = fmaxf(m, sv[i]);
                m = warp_max(m);
                float l = 0.f;
#pragma unroll
                for (int i = 0; i < 8; i++) { sv[i] = exp_diff(sv[i], m); l += sv[i]; }
                l = warp_sum(l);
                if (lane < 2) st_async_v2(mapa(sb + OFF_ML + (rank * 8 + warp) * 8, lane), m, l, mapa(mlbar, lane));
                mbar_wait_cluster(mlbar, 0);
                const float2 ml = lds_f32x2(sb + OFF_ML + (lane & 15) * 8);
                const float M = warp_max(ml.x);
                float L = exp_diff(ml.x, M) * ml.y;
#pragma unroll
                for (int ofs = 8; ofs > 0; ofs >>= 1) L += __shfl_xor_sync(0xffffffffu, L, ofs);
                const float f = __fdiv_rn(exp_diff(m, M), L);
#pragma unroll
                for (int j = 0; j < 4; j++) sts_u32(sb + OFF_P + t * 128 + j * 32 + w4 * 8 + hf * 4, pack_bf16(sv[2 * j] * f, sv[2 * j + 1] * f));
            }
            const uint32_t vbase = pin(sb + (8 * (mi >> 1) + r) * 256 + grp * 128 + ((2 * w4) ^ (mi & 1) ^ (r >> 2) ^ (2 * (r & 3) + grp)) * 16);
            const uint32_t wbase0 = pin(sb + (warp >> 1) * 4096 + (r + 8 * (mi >> 1)) * 128 + ((4 * (warp & 1) + (mi & 1)) ^ r) * 16);
            const uint32_t wbase1 = pin(wbase0 ^ 32);
            const uint32_t o_loc = pin(sb + OFF_OPART + rank * 512 + (warp * 8 + g) * 8);
            const uint32_t o_dst = pin(mapa(o_loc, rank ^ 1)), o_bar = pin(mapa(obar + c * 8, rank ^ 1));
            const uint32_t o_src = pin(sb + OFF_OPART + lane * 16), obar_p = pin(obar);
            const uint32_t first = pin((uint32_t)(c == 0)), cq = pin((uint32_t)c);
            const bool lane0 = pin((uint32_t)(lane == 0)), odd = pin((uint32_t)(c & 1));
            unsigned long long* const acc_p = pin(p.acc + b * DM + rank * 256 + tid);
            __nv_bfloat16* const out_p = pin(p.out + b * DM + rank * 256 + warp * 32 + c * 8 + g);
            const bool feed = pin((uint32_t)((c >> 1) == (g & 1))), low = pin((uint32_t)(c < 2));
            bar_sync(1, 256);
            float oc[4][4];
#pragma unroll
            for (int j = 0; j < 4; j++) { oc[j][0] = oc[j][1] = oc[j][2] = oc[j][3] = 0.f; }
            {
                auto pv_tile = [&](uint32_t vb, const uint4& p0, const uint4& p1) {
                    uint32_t a[4][4];
#pragma unroll
                    for (int j = 0; j < 4; j++) ldsm4t(a[j], vb + j * 4096);
                    mma16816(oc[0], a[0], p0.x, p0.y);
                    mma16816(oc[1], a[1], p0.z, p0.w);
                    mma16816(oc[2], a[2], p1.x, p1.y);
                    mma16816(oc[3], a[3], p1.z, p1.w);
                };
                uint32_t psrc = sb + OFF_P + c * 32;
                uint4 pe[EG][2];
#pragma unroll
                for (int j = 0; j < EG; j++) {
                    pe[j][0] = pe[j][1] = make_uint4(0u, 0u, 0u, 0u);
                    if (feed) { pe[j][0] = lds_v4(psrc + (32 - EG + j) * 128); pe[j][1] = lds_v4(psrc + (32 - EG + j) * 128 + 16); }
                }
                int s = 36 % NST, ph = (36 / NST) & 1;
#pragma unroll 1
                for (int it = 0; it < 32 - EG; it++) {
                    uint4 p0 = make_uint4(0u, 0u, 0u, 0u), p1 = p0;
                    if (feed) { p0 = lds_v4(psrc); p1 = lds_v4(psrc + 16); }
                    psrc += 128;
                    mbar_wait(full0 + 8 * s, ph);
                    pv_tile(vbase + s * STAGE, p0, p1);
                    if (it < 36 - NST) release_stage<1>(empty0 + 8 * s, lane);
                    if (++s == NST) { s = 0; ph ^= 1; }
                }
#pragma unroll
                for (int j = 0; j < EG; j++) {
                    mbar_wait(full0 + 8 * (NST - 4 - EG + j), (72 / NST - 1) & 1);
                    pv_tile(vbase + (NST - 4 - EG + j) * STAGE, pe[j][0], pe[j][1]);
                }
            }
            asm volatile("{\n.reg .pred p;\nsetp.ne.u32 p, %5, 0;\n"
                         "@p st.async.shared::cluster.mbarrier::complete_tx::bytes.v2.f32 [%0], {%1, %2}, [%3];\n"
                         "@p st.shared.v2.f32 [%4], {%1, %2};\n}"
                         ::"r"(o_dst),
                           "f"((((oc[0][0] + oc[0][3]) + (oc[1][0] + oc[1][3])) + (oc[2][0] + oc[2][3])) + (oc[3][0] + oc[3][3])),
                           "f"((((oc[0][1] + oc[0][2]) + (oc[1][1] + oc[1][2])) + (oc[2][1] + oc[2][2])) + (oc[3][1] + oc[3][2])),
                           "r"(o_bar), "r"(o_loc), "r"(first) : "memory");
            __syncwarp();
            if (lane0) mbar_arrive<1>(obar_p);
            mbar_wait_cluster(obar_p, 0);
            uint32_t of[8][2];
            {
                const uint4 u = lds_v4(o_src), v = lds_v4(o_src + 512);
                const uint32_t f0 = pack_bf16(__uint_as_float(u.x) + __uint_as_float(v.x), __uint_as_float(u.z) + __uint_as_float(v.z));
                const uint32_t f1 = pack_bf16(__uint_as_float(u.y) + __uint_as_float(v.y), __uint_as_float(u.w) + __uint_as_float(v.w));
#pragma unroll
                for (int t = 0; t < 8; t++) {
                    of[t][0] = __shfl_sync(0xffffffffu, f0, 4 * t + cq);
                    of[t][1] = __shfl_sync(0xffffffffu, f1, 4 * t + cq);
                }
            }
            float y0[4] = {0.f, 0.f, 0.f, 0.f}, y1[4] = {0.f, 0.f, 0.f, 0.f};
#pragma unroll
            for (int t = 0; t < 4; t++) {
                uint32_t a[4][4];
                mbar_wait(full0 + 8 * (NST - 4 + t), (72 / NST - 1) & 1);
#pragma unroll
                for (int j = 0; j < 4; j++) ldsm4t(a[j], ((j & 1) ? wbase1 : wbase0) + (NST - 4 + t) * STAGE + (j >> 1) * 2048);
                mma16816(y0, a[0], of[2 * t][0], of[2 * t][1]);
                mma16816(y1, a[1], of[2 * t][0], of[2 * t][1]);
                mma16816(y0, a[2], of[2 * t + 1][0], of[2 * t + 1][1]);
                mma16816(y1, a[3], of[2 * t + 1][0], of[2 * t + 1][1]);
            }
            const float z0 = odd ? y0[2] : y0[0], z1 = odd ? y1[2] : y1[0];
            contribute(acc_p, out_p, low ? z0 : z1, needs_float_path((fabsf(y0[0]) + fabsf(y0[2])) + (fabsf(y1[0]) + fabsf(y1[2]))));
        }
    } else {
        const int fj = cta - NATT;
        const int sh1 = fj & 1;
        const int T1 = 32 + sh1, T2 = (fj == NFFN - 1) ? (FF - (NFFN - 1) * FSL) / 16 : FSL / 16;
        uint4 xs0, xs1;
        uint32_t bias_raw[6], res_raw[6];
        if (warp < 8) {
            xs0 = ldg_v4(p.x + (warp & 1) * DM + lane * 16);
            xs1 = ldg_v4(p.x + (warp & 1) * DM + lane * 16 + 8);
#pragma unroll
            for (int j = 0; j < 6; j++) bias_raw[j] = ldg_u16(p.b1 + min(fj * FSL + (warp + 8 * (j >> 1)) * 16 + (j & 1) * 8 + g, FF - 1));
#pragma unroll
            for (int j = 0; j < 6; j++) res_raw[j] = ldg_u16((j < 4 ? p.x + (j >> 1) * DM : p.b2) + warp * 64 + c * 16 + (j & 1) * 8 + g);
        } else if (lane == 0) {
            prefetch_map(&maps.w1);
#pragma unroll
            for (int s = 0; s < NST; s++) { mbar_init(full0 + 8 * s, 1); mbar_init(empty0 + 8 * s, 8); }
            mbar_init_fence();
        }
        __syncthreads();
        if (warp == 8) {
            if (lane == 0) {
                const char* p2 = (const char*)(p.w2 + (size_t)fj * FSL * DM);
                const uint64_t pol = policy_evict_first();
                int s = 0, ph = 1;
#pragma unroll 1
                for (int i = 0; i < T1 + T2 + NST; i++) {
                    mbar_wait_bounded(empty0 + 8 * s, ph);
                    if (i < T1) {
                        mbar_expect_tx(full0 + 8 * s, 16 * FSL * 2);
                        tensor_load(sb + s * STAGE, &maps.w1, fj * (FSL / 2), i * 16 - sh1, full0 + 8 * s, pol);
                    } else if (i < T1 + T2) {
                        mbar_expect_tx(full0 + 8 * s, STAGE);
                        bulk_load(sb + s * STAGE, p2 + (size_t)(i - T1) * STAGE, STAGE, full0 + 8 * s, pol);
                    }
                    if (++s == NST) { s = 0; ph ^= 1; }
                }
            }
        } else {
            const uint32_t xn_s = sb + OFF_QPART;
            const uint32_t g_s = xn_s + 2 * 1056;
            if (warp < 2) {
                float mean_bf, sd_bf, xn[16];
                ln_stats(xs0, xs1, mean_bf, sd_bf);
                unpack8(xs0, xn); unpack8(xs1, xn + 8);
#pragma unroll
                for (int i = 0; i < 16; i++) sts_u16(xn_s + warp * 1056 + (lane * 16 + i + sh1) * 2, pack_bf16(ln_apply(xn[i], mean_bf, sd_bf), 0.f));
                if (lane < 16) sts_u16(xn_s + warp * 1056 + (lane == 15 && sh1 ? 0 : DM + sh1 + lane) * 2, 0);
            }
            bar_sync(1, 256);
            int s = 0, ph = 0;
            float hacc[3][4];
#pragma unroll
            for (int j = 0; j < 3; j++) { hacc[j][0] = hacc[j][1] = hacc[j][2] = hacc[j][3] = 0.f; }
            uint32_t aoff[3];
#pragma unroll
            for (int j = 0; j < 3; j++) aoff[j] = (r + 8 * (mi >> 1)) * (FSL * 2) + min(2 * (warp + 8 * j) + (mi & 1), FSL / 8 - 1) * 16;
#pragma unroll 1
            for (int i = 0; i < T1; i++) {
                uint32_t f0 = 0, f1 = 0;
                if (g < 2) { f0 = lds_u32(xn_s + g * 1056 + i * 32 + c * 4); f1 = lds_u32(xn_s + g * 1056 + i * 32 + 16 + c * 4); }
                mbar_wait(full0 + 8 * s, ph);
#pragma unroll
                for (int j = 0; j < 3; j++) {
                    uint32_t a[4];
                    ldsm4t(a, sb + s * STAGE + aoff[j]);
                    mma16816(hacc[j], a, f0, f1);
                }
                release_stage<1>(empty0 + 8 * s, lane);
                if (++s == NST) { s = 0; ph ^= 1; }
            }
            if (c == 0) {
#pragma unroll
                for (int j = 0; j < 3; j++)
#pragma unroll
                    for (int hf = 0; hf < 2; hf++) {
                        const int f = (warp + 8 * j) * 16 + hf * 8 + g;
                        if (f < FSL) {
                            const float bias = bf_lo(bias_raw[2 * j + hf]);
#pragma unroll
                            for (int bb = 0; bb < 2; bb++) {
                                const float hv = rbf(rbf(hacc[j][2 * hf + bb]) + bias);
                                const float inner = 0.7978845608028654f * (hv + 0.044715f * hv * hv * hv);
                                sts_u16(g_s + bb * 704 + f * 2, pack_bf16(0.5f * hv * (1.f + tanhf(inner)), 0.f));
                            }
                        }
                    }
            }
            bar_sync(1, 256);
            float y[2][4][4];
#pragma unroll
            for (int bb = 0; bb < 2; bb++)
#pragma unroll
                for (int j = 0; j < 4; j++) { y[bb][j][0] = y[bb][j][1] = y[bb][j][2] = y[bb][j][3] = 0.f; }
            const int sh = (g & 1) * 16;
#pragma unroll 1
            for (int i = 0; i < T2; i++) {
                uint32_t f[2][2] = {{0u, 0u}, {0u, 0u}};
                if (diag) {
#pragma unroll
                    for (int bb = 0; bb < 2; bb++) {
                        f[bb][0] = lds_u16(g_s + bb * 704 + (i * 16 + g) * 2) << sh;
                        f[bb][1] = lds_u16(g_s + bb * 704 + (i * 16 + 8 + g) * 2) << sh;
                    }
                }
                const uint32_t wb = sb + s * STAGE + (r + 8 * (mi >> 1)) * 1024 + warp * 128 + (((mi & 1) * 4) ^ r) * 16;
                mbar_wait(full0 + 8 * s, ph);
#pragma unroll
                for (int j = 0; j < 4; j++) {
                    uint32_t a[4];
                    ldsm4t(a, wb ^ (j << 4));
                    mma16816(y[0][j], a, f[0][0], f[0][1]);
                    mma16816(y[1][j], a, f[1][0], f[1][1]);
                }
                release_stage<1>(empty0 + 8 * s, lane);
                if (++s == NST) { s = 0; ph ^= 1; }
            }
#pragma unroll
            for (int bb = 0; bb < 2; bb++) {
                float yy[16];
#pragma unroll
                for (int j = 0; j < 4; j++) { yy[2 * j] = y[bb][j][0]; yy[2 * j + 1] = y[bb][j][1]; yy[8 + 2 * j] = y[bb][j][2]; yy[8 + 2 * j + 1] = y[bb][j][3]; }
                float2 yo = fold8(yy);
                if (fj == 0) {
                    yo.x += bf_lo(res_raw[2 * bb]) + bf_lo(res_raw[4]);
                    yo.y += bf_lo(res_raw[2 * bb + 1]) + bf_lo(res_raw[5]);
                }
                const int n0 = bb * DM + warp * 64 + c * 16;
                unsigned long long* a = p.acc + (n0 & ~31) + 4 * g + 2 * (c & 1);
                const bool fp = needs_float_path(warp_max(fabsf(yo.x) + fabsf(yo.y)));
                contribute(a, p.out + n0 + g, yo.x, fp);
                contribute(a + 1, p.out + n0 + 8 + g, yo.y, fp);
            }
        }
    }
}

typedef CUresult (*EncodeFn)(CUtensorMap*, CUtensorMapDataType, cuuint32_t, void*, const cuuint64_t*, const cuuint64_t*,
                             const cuuint32_t*, const cuuint32_t*, CUtensorMapInterleave, CUtensorMapSwizzle,
                             CUtensorMapL2promotion, CUtensorMapFloatOOBfill);

void encode_2d(EncodeFn fn, CUtensorMap* map, CUtensorMapDataType dt, const void* base, uint64_t cols, uint64_t rows,
               uint64_t pitch_bytes, uint32_t box_cols, uint32_t box_rows, CUtensorMapSwizzle sw) {
    const cuuint64_t dims[2] = {cols, rows}, strides[1] = {pitch_bytes};
    const cuuint32_t box[2] = {box_cols, box_rows}, estr[2] = {1, 1};
    fn(map, dt, 2, const_cast<void*>(base), dims, strides, box, estr, CU_TENSOR_MAP_INTERLEAVE_NONE, sw,
       CU_TENSOR_MAP_L2_PROMOTION_NONE, CU_TENSOR_MAP_FLOAT_OOB_FILL_NONE);
}

}

extern "C" void kernel_launch(void* const* d_in, const int* in_sizes, int n_in, void* d_out, int out_size) {
    (void)in_sizes; (void)n_in; (void)out_size;
    typedef const __nv_bfloat16* P;
    static EncodeFn encode = nullptr;
    static void* acc = nullptr;
    static double stream_ns = 0.0;
    if (!encode) {
        cudaFuncSetAttribute(fused_decode_kernel, cudaFuncAttributeMaxDynamicSharedMemorySize, SMEM_BYTES);
        cudaDriverEntryPointQueryResult st;
        cudaGetDriverEntryPoint("cuTensorMapEncodeTiled", (void**)&encode, cudaEnableDefault, &st);
        cudaGetSymbolAddress(&acc, g_acc);
        int dev = 0, sms = 0, khz = 0, bits = 0;
        cudaGetDevice(&dev);
        cudaDeviceGetAttribute(&sms, cudaDevAttrMultiProcessorCount, dev);
        cudaDeviceGetAttribute(&khz, cudaDevAttrMemoryClockRate, dev);
        cudaDeviceGetAttribute(&bits, cudaDevAttrGlobalMemoryBusWidth, dev);
        const double bytes = 2.0 * (2.0 * 2 * NH * WIN * DH + 2.0 * DM * NH * DH + 2.0 * DM * FF);
        if (sms >= NCTA && khz > 0 && bits > 0) stream_ns = bytes / (2.0 * khz * 1e-6 * bits / 8);
    }
    Params p;
    p.kc = (P)d_in[1]; p.x = (P)d_in[0];
    p.acc = (unsigned long long*)acc; p.out = (__nv_bfloat16*)d_out;
    p.w2 = (P)d_in[8]; p.b1 = (P)d_in[7]; p.b2 = (P)d_in[9];
    p.t_end = (int)(stream_ns * 1.005); p.t_kv = (int)(stream_ns / 62); p.t_wo = (int)(stream_ns / 114); p.t_stag = (int)(stream_ns / 48);
    Maps maps;
    encode_2d(encode, &maps.wq, CU_TENSOR_MAP_DATA_TYPE_BFLOAT16, d_in[3], NH * DH, DM, NH * DH * 2, DH, 64,
              CU_TENSOR_MAP_SWIZZLE_NONE);
    encode_2d(encode, &maps.v, CU_TENSOR_MAP_DATA_TYPE_BFLOAT16, d_in[2], 64, (uint64_t)2 * 2 * NH * SK, 128, 64, 128,
              CU_TENSOR_MAP_SWIZZLE_128B);
    {
        const cuuint64_t dims[3] = {64, NH * DH, DM / 64}, strides[2] = {DM * 2, 128};
        const cuuint32_t box[3] = {64, 32, 4}, estr[3] = {1, 1, 1};
        encode(&maps.wo, CU_TENSOR_MAP_DATA_TYPE_BFLOAT16, 3, d_in[4], dims, strides, box, estr, CU_TENSOR_MAP_INTERLEAVE_NONE,
               CU_TENSOR_MAP_SWIZZLE_128B, CU_TENSOR_MAP_L2_PROMOTION_NONE, CU_TENSOR_MAP_FLOAT_OOB_FILL_NONE);
    }
    encode_2d(encode, &maps.w1, CU_TENSOR_MAP_DATA_TYPE_UINT32, d_in[6], FF / 2, DM, FF * 2, FSL / 2, 16,
              CU_TENSOR_MAP_SWIZZLE_NONE);
    fused_decode_kernel<<<NCTA, NTHREADS, SMEM_BYTES>>>(p, maps);
}
```

```cpp
#include <cuda.h>
#include <cuda_runtime.h>
#include <cuda_bf16.h>
#include <stdint.h>

namespace {

constexpr int DM = 512, NH = 32, SK = 16384, WIN = 4096, DH = 128, FF = 1376;
constexpr int NATT = 128, NFFN = 4, NCTA = NATT + NFFN;
constexpr int NPROD = NH + NFFN;
constexpr int FSL = 352;
constexpr int NST = 8;
constexpr int STAGE = 16384;
constexpr int PRE = 2;
constexpr int EG = 4;
constexpr int NTHREADS = 288;
static_assert(NST % 2 == 0 && 72 % NST == 0 && EG + 4 <= NST, "ring geometry");

constexpr int OFF_QPART = NST * STAGE;
constexpr int OFF_S = OFF_QPART, OFF_P = OFF_QPART + 4096;
constexpr int OFF_OPART = OFF_QPART + 8192;
constexpr int OFF_ML = OFF_OPART + 1024;
constexpr int OFF_QBF = OFF_ML + 128;
constexpr int OFF_BAR = OFF_QBF + 256;
constexpr int SMEM_BYTES = OFF_BAR + (2 * NST + 3) * 8;

constexpr int ACC_PITCH = 40;
__device__ __align__(256) unsigned long long g_acc[2 * DM / 8 * ACC_PITCH];
__device__ __forceinline__ int acc_slot(int i) { return (i >> 3) * ACC_PITCH + (i & 7); }

struct Params {
    const __nv_bfloat16 *kc, *x;
    unsigned long long* acc;
    __nv_bfloat16* out;
    const __nv_bfloat16 *w2, *b1, *b2;
    int t_end, t_tile;
};
struct Maps {
    alignas(64) CUtensorMap wq, v, wo, w1;
};

__device__ __forceinline__ void mbar_init(uint32_t bar, uint32_t cnt) {
    asm volatile("mbarrier.init.shared::cta.b64 [%0], %1;" ::"r"(bar), "r"(cnt) : "memory");
}
__device__ __forceinline__ void mbar_init_fence() { asm volatile("fence.mbarrier_init.release.cluster;" ::: "memory"); }
__device__ __forceinline__ void mbar_expect_tx(uint32_t bar, uint32_t bytes) {
    asm volatile("mbarrier.arrive.expect_tx.shared::cta.b64 _, [%0], %1;" ::"r"(bar), "r"(bytes) : "memory");
}
template <int N>
__device__ __forceinline__ void mbar_arrive(uint32_t bar) {
    asm volatile("mbarrier.arrive.shared::cta.b64 _, [%0], %1;" ::"r"(bar), "n"(N) : "memory");
}
template <int N>
__device__ __forceinline__ void release_stage(uint32_t bar, int lane) {
    asm volatile("fence.proxy.async.shared::cta;" ::: "memory");
    __syncwarp();
    if (lane == 0) mbar_arrive<N>(bar);
}
#define WAIT_LIMIT (1u << 18)
__device__ __forceinline__ void mbar_wait_bounded(uint32_t bar, uint32_t parity) {
    uint32_t ok, n = 0;
    do {
        if (++n > WAIT_LIMIT) __trap();
        asm volatile(
            "{\n.reg .pred p;\nmbarrier.try_wait.parity.shared::cta.b64 p, [%1], %2;\nselp.u32 %0, 1, 0, p;\n}\n"
            : "=r"(ok) : "r"(bar), "r"(parity) : "memory");
    } while (!ok);
}
__device__ __forceinline__ void mbar_wait(uint32_t bar, uint32_t parity) {
    asm volatile(
        "{\n.reg .pred p;\nWAIT_LOOP:\nmbarrier.try_wait.parity.shared::cta.b64 p, [%0], %1;\n@!p bra WAIT_LOOP;\n}\n"
        ::"r"(bar), "r"(parity) : "memory");
}
__device__ __forceinline__ void mbar_wait_cluster(uint32_t bar, uint32_t parity) {
    asm volatile(
        "{\n.reg .pred p;\nWAIT_LOOP:\nmbarrier.try_wait.parity.acquire.cluster.shared::cta.b64 p, [%0], %1;\n@!p bra WAIT_LOOP;\n}\n"
        ::"r"(bar), "r"(parity) : "memory");
}
__device__ __forceinline__ uint64_t policy_evict_first() {
    uint64_t pol;
    asm volatile("createpolicy.fractional.L2::evict_first.b64 %0, 1.0;" : "=l"(pol));
    return pol;
}
__device__ __forceinline__ void bulk_load(uint32_t dst, const void* src, uint32_t bytes, uint32_t bar, uint64_t pol) {
    asm volatile("cp.async.bulk.shared::cluster.global.mbarrier::complete_tx::bytes.L2::cache_hint [%0], [%1], %2, [%3], %4;"
                 ::"r"(dst), "l"(src), "r"(bytes), "r"(bar), "l"(pol) : "memory");
}
__device__ __forceinline__ void tensor_load(uint32_t dst, const CUtensorMap* map, int cx, int cy, uint32_t bar) {
    asm volatile("cp.async.bulk.tensor.2d.shared::cluster.global.mbarrier::complete_tx::bytes [%0], [%1, {%2, %3}], [%4];"
                 ::"r"(dst), "l"(map), "r"(cx), "r"(cy), "r"(bar) : "memory");
}
__device__ __forceinline__ void tensor_load(uint32_t dst, const CUtensorMap* map, int cx, int cy, uint32_t bar, uint64_t pol) {
    asm volatile("cp.async.bulk.tensor.2d.shared::cluster.global.mbarrier::complete_tx::bytes.L2::cache_hint [%0], [%1, {%2, %3}], [%4], %5;"
                 ::"r"(dst), "l"(map), "r"(cx), "r"(cy), "r"(bar), "l"(pol) : "memory");
}
__device__ __forceinline__ void tensor_load3(uint32_t dst, const CUtensorMap* map, int cx, int cy, int cz, uint32_t bar) {
    asm volatile("cp.async.bulk.tensor.3d.shared::cluster.global.mbarrier::complete_tx::bytes [%0], [%1, {%2, %3, %4}], [%5];"
                 ::"r"(dst), "l"(map), "r"(cx), "r"(cy), "r"(cz), "r"(bar) : "memory");
}
__device__ __forceinline__ void prefetch_map(const CUtensorMap* map) {
    asm volatile("prefetch.tensormap [%0];" ::"l"(map) : "memory");
}
__device__ __forceinline__ uint4 ldg_v4(const void* p) {
    uint4 v;
    asm volatile("ld.global.v4.u32 {%0,%1,%2,%3}, [%4];" : "=r"(v.x), "=r"(v.y), "=r"(v.z), "=r"(v.w) : "l"(p) : "memory");
    return v;
}
__device__ __forceinline__ uint32_t ldg_u16(const void* p) {
    uint16_t v;
    asm volatile("ld.global.u16 %0, [%1];" : "=h"(v) : "l"(p) : "memory");
    return v;
}
__device__ __forceinline__ void ldsm4(uint32_t (&r)[4], uint32_t addr) {
    asm volatile("ldmatrix.sync.aligned.m8n8.x4.shared.b16 {%0,%1,%2,%3}, [%4];"
                 : "=r"(r[0]), "=r"(r[1]), "=r"(r[2]), "=r"(r[3]) : "r"(addr) : "memory");
}
__device__ __forceinline__ void ldsm4t(uint32_t (&r)[4], uint32_t addr) {
    asm volatile("ldmatrix.sync.aligned.m8n8.x4.trans.shared.b16 {%0,%1,%2,%3}, [%4];"
                 : "=r"(r[0]), "=r"(r[1]), "=r"(r[2]), "=r"(r[3]) : "r"(addr) : "memory");
}
__device__ __forceinline__ void mma16816(float (&d)[4], const uint32_t (&a)[4], uint32_t b0, uint32_t b1) {
    asm volatile(
        "mma.sync.aligned.m16n8k16.row.col.f32.bf16.bf16.f32 {%0,%1,%2,%3}, {%4,%5,%6,%7}, {%8,%9}, {%0,%1,%2,%3};"
        : "+f"(d[0]), "+f"(d[1]), "+f"(d[2]), "+f"(d[3])
        : "r"(a[0]), "r"(a[1]), "r"(a[2]), "r"(a[3]), "r"(b0), "r"(b1));
}
__device__ __forceinline__ uint32_t mapa(uint32_t addr, uint32_t rank) {
    uint32_t r;
    asm("mapa.shared::cluster.u32 %0, %1, %2;" : "=r"(r) : "r"(addr), "r"(rank));
    return r;
}
__device__ __forceinline__ void st_async_v4(uint32_t addr, float a, float b, float c, float d, uint32_t bar) {
    asm volatile("st.async.shared::cluster.mbarrier::complete_tx::bytes.v4.f32 [%0], {%1,%2,%3,%4}, [%5];"
                 ::"r"(addr), "f"(a), "f"(b), "f"(c), "f"(d), "r"(bar) : "memory");
}
__device__ __forceinline__ void st_async_v2(uint32_t addr, float a, float b, uint32_t bar) {
    asm volatile("st.async.shared::cluster.mbarrier::complete_tx::bytes.v2.f32 [%0], {%1,%2}, [%3];"
                 ::"r"(addr), "f"(a), "f"(b), "r"(bar) : "memory");
}
__device__ __forceinline__ uint32_t lds_u16(uint32_t addr) {
    uint16_t v;
    asm volatile("ld.shared.u16 %0, [%1];" : "=h"(v) : "r"(addr) : "memory");
    return v;
}
__device__ __forceinline__ uint32_t lds_u32(uint32_t addr) {
    uint32_t v;
    asm volatile("ld.shared.u32 %0, [%1];" : "=r"(v) : "r"(addr) : "memory");
    return v;
}
__device__ __forceinline__ float2 lds_f32x2(uint32_t addr) {
    float2 v;
    asm volatile("ld.shared.v2.f32 {%0,%1}, [%2];" : "=f"(v.x), "=f"(v.y) : "r"(addr) : "memory");
    return v;
}
__device__ __forceinline__ uint4 lds_v4(uint32_t addr) {
    uint4 v;
    asm volatile("ld.shared.v4.u32 {%0,%1,%2,%3}, [%4];" : "=r"(v.x), "=r"(v.y), "=r"(v.z), "=r"(v.w) : "r"(addr) : "memory");
    return v;
}
__device__ __forceinline__ void sts_u16(uint32_t addr, uint32_t v) {
    asm volatile("st.shared.u16 [%0], %1;" ::"r"(addr), "h"((uint16_t)v) : "memory");
}
__device__ __forceinline__ void sts_u32(uint32_t addr, uint32_t v) {
    asm volatile("st.shared.u32 [%0], %1;" ::"r"(addr), "r"(v) : "memory");
}
__device__ __forceinline__ void bar_sync(int id, int n) { asm volatile("bar.sync %0, %1;" ::"r"(id), "r"(n) : "memory"); }
__device__ __forceinline__ void cluster_arrive() { asm volatile("barrier.cluster.arrive.relaxed.aligned;" ::: "memory"); }
__device__ __forceinline__ void cluster_wait() { asm volatile("barrier.cluster.wait.acquire.aligned;" ::: "memory"); }

__device__ __forceinline__ uint32_t now_ns() {
    uint32_t t;
    asm volatile("mov.u32 %0, %%globaltimer_lo;" : "=r"(t));
    return t;
}
__device__ __forceinline__ uint32_t pin(uint32_t v) { return __shfl_sync(0xffffffffu, v, threadIdx.x & 31); }
template <class T>
__device__ __forceinline__ T* pin(T* q) {
    const uint64_t v = (uint64_t)q;
    return (T*)(((uint64_t)pin((uint32_t)(v >> 32)) << 32) | pin((uint32_t)v));
}

__device__ __forceinline__ uint32_t pack_bf16(float lo, float hi) {
    uint32_t r;
    asm("cvt.rn.bf16x2.f32 %0, %1, %2;" : "=r"(r) : "f"(hi), "f"(lo));
    return r;
}
__device__ __forceinline__ float bf_lo(uint32_t v) { return __uint_as_float(v << 16); }
__device__ __forceinline__ float bf_hi(uint32_t v) { return __uint_as_float(v & 0xffff0000u); }
__device__ __forceinline__ float rbf(float x) { return bf_lo(pack_bf16(x, 0.f)); }
__device__ __forceinline__ float exp_diff(float a, float b) {
    float r;
    asm("ex2.approx.ftz.f32 %0, %1;" : "=f"(r) : "f"((a - b) * 1.4426950408889634f));
    return r;
}
__device__ __forceinline__ float warp_max(float x) {
    int k = __float_as_int(x);
    k ^= (k >> 31) & 0x7fffffff;
    k = __reduce_max_sync(0xffffffffu, k);
    k ^= (k >> 31) & 0x7fffffff;
    return __int_as_float(k);
}
__device__ __forceinline__ float warp_sum(float x) {
#pragma unroll
    for (int o = 16; o > 0; o >>= 1) x += __shfl_xor_sync(0xffffffffu, x, o);
    return x;
}
__device__ __forceinline__ void unpack8(const uint4& v, float* f) {
    f[0] = bf_lo(v.x); f[1] = bf_hi(v.x); f[2] = bf_lo(v.y); f[3] = bf_hi(v.y);
    f[4] = bf_lo(v.z); f[5] = bf_hi(v.z); f[6] = bf_lo(v.w); f[7] = bf_hi(v.w);
}
__device__ __forceinline__ void ln_stats(const uint4& a, const uint4& b, float& mean_bf, float& sd_bf) {
    float f[16];
    unpack8(a, f); unpack8(b, f + 8);
    float s = 0.f;
#pragma unroll
    for (int i = 0; i < 16; i++) s += f[i];
    const float mean = warp_sum(s) * (1.f / DM);
    float q = 0.f;
#pragma unroll
    for (int i = 0; i < 16; i++) { const float d = f[i] - mean; q = fmaf(d, d, q); }
    const float var = warp_sum(q) * (1.f / DM);
    mean_bf = rbf(mean);
    sd_bf = rbf(__fsqrt_rn(rbf(rbf(var) + 1e-5f)));
}
__device__ __forceinline__ float ln_apply(float x, float mean_bf, float sd_bf) {
    return rbf(__fdiv_rn(rbf(x - mean_bf), sd_bf));
}
__device__ __forceinline__ float2 fold8(const float* c) {
    float v[8];
#pragma unroll
    for (int i = 0; i < 8; i++) v[i] = c[2 * i] + c[2 * (i ^ 1) + 1];
    const float w0 = v[0] + __shfl_xor_sync(0xffffffffu, v[2], 1);
    const float w1 = v[1] + __shfl_xor_sync(0xffffffffu, v[3], 1);
    const float w4 = v[4] + __shfl_xor_sync(0xffffffffu, v[6], 1);
    const float w5 = v[5] + __shfl_xor_sync(0xffffffffu, v[7], 1);
    return make_float2(w0 + __shfl_xor_sync(0xffffffffu, w4, 2), w1 + __shfl_xor_sync(0xffffffffu, w5, 2));
}

__device__ __forceinline__ bool needs_float_path(float mag) {
    return !(mag < 0x1p13f) || mag < 0x1p-12f;
}
__device__ __forceinline__ bool add_fixed(unsigned long long* a, __nv_bfloat16* o, long long v, bool skip, float& sum) {
    uint32_t lo = (uint32_t)v, hi = (uint32_t)(v >> 32) + 0x1000000u;
    asm volatile("{\n.reg .pred p;\n.reg .b64 t;\nsetp.eq.u32 p, %3, 0;\nmov.b64 t, {%0, %1};\n"
                 "@p atom.relaxed.gpu.global.add.u64 t, [%2], t;\nmov.b64 {%0, %1}, t;\n}"
                 : "+r"(lo), "+r"(hi) : "l"(a), "r"((uint32_t)skip) : "memory");
    const unsigned long long r = (((unsigned long long)hi << 32) | lo) + ((unsigned long long)v + (1ull << 31) - ((unsigned long long)(NPROD - 1) << 56));
    const uint32_t t = (uint32_t)(r >> 32) + 0x800000u;
    const float frac = (float)(int)((uint32_t)r ^ 0x80000000u) * 0x1p-36f;
    const uint32_t pk = pack_bf16(fmaf((float)(int)(r >> 32), 0x1p-4f, frac), 0.f);
    asm volatile("{\n.reg .pred p, q;\nsetp.eq.u32 q, %4, 0;\nsetp.lt.and.u32 p, %3, 0x1000000, q;\n"
                 "@p st.global.u16 [%0], %1;\n@p st.global.u64 [%2], 0;\n}"
                 ::"l"(o), "h"((uint16_t)pk), "l"(a), "r"(t), "r"((uint32_t)skip) : "memory");
    sum = fmaf((float)(int)((uint32_t)(r >> 32) ^ 0x80000000u), 0x1p-4f, frac);
    return (t ^ 0x80000000u) < 0x1000000u;
}
__device__ __noinline__ void finish_flagged(unsigned long long* a, __nv_bfloat16* o, float sum) {
    float side;
    asm volatile("fence.acq_rel.gpu;" ::: "memory");
    asm volatile("atom.relaxed.gpu.global.exch.b32 %0, [%1+64], 0;" : "=f"(side) : "l"(a) : "memory");
    asm volatile("st.global.u16 [%0], %1;" ::"l"(o), "h"((uint16_t)pack_bf16(sum + side, 0.f)) : "memory");
    asm volatile("st.global.u64 [%0], %1;" ::"l"(a), "l"(0ull) : "memory");
}
__device__ __noinline__ void add_float(unsigned long long* a, __nv_bfloat16* o, float y) {
    asm volatile("red.relaxed.gpu.global.add.f32 [%0+64], %1;" ::"l"(a), "f"(y) : "memory");
    asm volatile("red.release.gpu.global.or.b64 [%0], %1;" ::"l"(a), "l"(1ull << 63) : "memory");
    float sum;
    if (add_fixed(a, o, 0, false, sum)) finish_flagged(a, o, sum);
}
__device__ __forceinline__ void contribute(unsigned long long* a, __nv_bfloat16* o, float y, bool float_path) {
    float sum;
    const bool flagged = add_fixed(a, o, __float2ll_rn(y * 0x1p36f), float_path, sum);
    if (__builtin_expect(float_path, 0)) add_float(a, o, y);
    else if (__builtin_expect(flagged, 0)) finish_flagged(a, o, sum);
}

__device__ __forceinline__ int work_of(int cl) {
    constexpr unsigned long long B = 0xaull | (0xffull << 12) | (0xffull << 28) | (0x7full << 43) | (0x7full << 57);
    const int b = (B >> cl) & 1, ones = __popcll(B << (63 - cl)) - b;
    return b ? NH + ones : cl - ones;
}

__global__ void __cluster_dims__(2, 1, 1) __launch_bounds__(NTHREADS, 1)
fused_decode_kernel(const __grid_constant__ Params p, const __grid_constant__ Maps maps) {
    extern __shared__ __align__(1024) unsigned char smem[];
    if (threadIdx.x == 0 && blockIdx.x < NATT) {
        const uint32_t ct = blockIdx.x;
        const char* k0 = (const char*)p.kc + (size_t)(uint32_t)(work_of(ct >> 1) * SK + (SK - WIN) + (ct & 1) * 64) * (DH * 2);
        asm volatile("cp.async.bulk.prefetch.L2.global.L2::cache_hint [%0], %1, %2;"
                     ::"l"(k0), "r"(STAGE), "l"(policy_evict_first()) : "memory");
    }
    const uint32_t sb = (uint32_t)__cvta_generic_to_shared(smem);
    const uint32_t full0 = sb + OFF_BAR, empty0 = full0 + NST * 8;
    const uint32_t qbar = empty0 + NST * 8, obar = qbar + 8, mlbar = obar + 8;
    const int tid = threadIdx.x, warp = tid >> 5, lane = tid & 31;
    const int cta = blockIdx.x;
    const int g = lane >> 2, c = lane & 3;
    const int r = lane & 7, mi = lane >> 3;
    const bool diag = (c == (g >> 1));

    if (cta < NATT) {
        const int rank = cta & 1, bh = work_of(cta >> 1), b = bh >> 5, h = bh & 31;
        if (warp == 8) {
            uint32_t due = now_ns();
            const int row0 = bh * SK + (SK - WIN) + rank * 64;
            const char* kp = (const char*)(p.kc + (size_t)row0 * DH);
            const uint64_t pol = policy_evict_first();
            if (lane == 0) {
#pragma unroll
                for (int s = 0; s < NST; s++) mbar_init(full0 + 8 * s, 1);
                mbar_init_fence();
#pragma unroll
                for (int j = 0; j < PRE; j++) {
                    mbar_expect_tx(full0 + 8 * (4 + j), STAGE);
                    bulk_load(sb + (4 + j) * STAGE, kp + j * (2 * STAGE), STAGE, full0 + 8 * (4 + j), pol);
                }
#pragma unroll
                for (int s = 0; s < 4; s++) {
                    mbar_expect_tx(full0 + 8 * s, STAGE);
                    tensor_load(sb + s * STAGE, &maps.wq, h * DH, rank * 256 + s * 64, full0 + 8 * s);
                }
#pragma unroll
                for (int j = PRE; j < NST - 4; j++) {
                    mbar_expect_tx(full0 + 8 * (4 + j), STAGE);
                    bulk_load(sb + (4 + j) * STAGE, kp + j * (2 * STAGE), STAGE, full0 + 8 * (4 + j), pol);
                }
#pragma unroll
                for (int s = 0; s < NST; s++) mbar_init(empty0 + 8 * s, 8);
                mbar_init(qbar, 1);
                mbar_init(obar, 1 + 8);
                mbar_init(mlbar, 1);
                mbar_init_fence();
                mbar_expect_tx(qbar, 16 * 512);
                mbar_expect_tx(obar, 512);
                mbar_expect_tx(mlbar, 16 * 8);
                due += p.t_end - (68 - NST) * p.t_tile - 3 * (p.t_tile >> 1) - ((((h * 13 + 30) & 31) * p.t_tile) >> 6);
                prefetch_map(&maps.v);
                prefetch_map(&maps.wo);
            }
            __syncwarp();
            cluster_arrive();
            cluster_wait();
            if (lane == 0) {
                int s = 0, ph = 0;
#pragma unroll 1
                for (int i = NST; i < 72; i++) {
                    mbar_wait_bounded(empty0 + 8 * s, ph);
                    mbar_expect_tx(full0 + 8 * s, STAGE);
                    for (uint32_t n = 0; (int)(now_ns() - due) < 0 && n < WAIT_LIMIT; n++) {}
                    if (i < 36) bulk_load(sb + s * STAGE, kp + (i - 4) * (2 * STAGE), STAGE, full0 + 8 * s, pol);
                    else if (i < 68) tensor_load(sb + s * STAGE, &maps.v, 0, 2 * row0 + (i - 36) * 256, full0 + 8 * s, pol);
                    else tensor_load3(sb + s * STAGE, &maps.wo, 0, h * DH + (i - 68) * 32, rank * 4, full0 + 8 * s);
                    due += i < 68 ? p.t_tile : p.t_tile >> 1;
                    if (++s == NST) { s = 0; ph ^= 1; }
                }
                mbar_wait_bounded(obar, 0);
#pragma unroll 1
                for (int t = NST - 4; t < NST; t++) mbar_wait_bounded(full0 + 8 * t, (72 / NST - 1) & 1);
            }
        } else {
            const int grp = warp >> 2, w4 = warp & 3;
            const bool e = g & 1;
            uint32_t qf[8][2];
            {
                const __nv_bfloat16* xb = p.x + b * DM;
                const uint4 xs0 = ldg_v4(xb + lane * 16), xs1 = ldg_v4(xb + lane * 16 + 8);
                uint32_t xr[4];
#pragma unroll
                for (int i = 0; i < 4; i++) xr[i] = ldg_u16(xb + rank * 256 + (grp + (i & 2)) * 64 + w4 * 16 + (i & 1) * 8 + g);
                cluster_arrive();
                float mean_bf, sd_bf;
                ln_stats(xs0, xs1, mean_bf, sd_bf);
#pragma unroll
                for (int i = 0; i < 4; i++)
                    xr[i] = diag ? __float_as_uint(ln_apply(bf_lo(xr[i]), mean_bf, sd_bf)) >> (e ? 0 : 16) : 0u;
                float o[8][4];
#pragma unroll
                for (int j = 0; j < 8; j++) { o[j][0] = o[j][1] = o[j][2] = o[j][3] = 0.f; }
                cluster_wait();
#pragma unroll
                for (int t = 0; t < 2; t++) {
                    const int s = grp + 2 * t;
                    const uint32_t wb = sb + s * STAGE + (w4 * 16 + r + 8 * (mi >> 1)) * 256 + (mi & 1) * 128 + r * 16;
                    mbar_wait(full0 + 8 * s, 0);
                    uint32_t a[8][4];
#pragma unroll
                    for (int j = 0; j < 8; j++) ldsm4t(a[j], wb ^ (j << 4));
#pragma unroll
                    for (int j = 0; j < 8; j++) mma16816(o[j], a[j], xr[2 * t], xr[2 * t + 1]);
                    release_stage<2>(empty0 + 8 * s, lane);
                }
                float lo[16], hi[16];
#pragma unroll
                for (int j = 0; j < 8; j++) { lo[2 * j] = o[j][0]; lo[2 * j + 1] = o[j][1]; hi[2 * j] = o[j][2]; hi[2 * j + 1] = o[j][3]; }
                const float2 u0 = fold8(lo), u1 = fold8(hi);
                const uint32_t slot = sb + OFF_QPART + (rank * 8 + warp) * 512 + lane * 16;
                st_async_v4(mapa(slot, 0), u0.x, u0.y, u1.x, u1.y, mapa(qbar, 0));
                st_async_v4(mapa(slot, 1), u0.x, u0.y, u1.x, u1.y, mapa(qbar, 1));
                if (tid < 128) {
                    mbar_wait_cluster(qbar, 0);
                    float sum = 0.f;
#pragma unroll
                    for (int i = 0; i < 16; i++) sum += __uint_as_float(lds_u32(sb + OFF_QPART + i * 512 + tid * 4));
                    const int col = (tid & 2) * 32 + ((tid >> 2) & 3) * 16 + (tid & 1) * 8 + (tid >> 4);
                    sts_u16(sb + OFF_QBF + col * 2, pack_bf16(sum, 0.f));
                }
                bar_sync(1, 256);
#pragma unroll
                for (int j = 0; j < 8; j++) {
                    qf[j][0] = lds_u32(sb + OFF_QBF + ((j ^ g) * 16) + c * 4);
                    qf[j][1] = lds_u32(sb + OFF_QBF + 128 + ((j ^ g) * 16) + c * 4);
                }
            }
            {
                const uint32_t koff = (w4 * 16 + r + 8 * (mi & 1)) * 256 + (mi >> 1) * 128 + r * 16;
                uint32_t sdst = sb + OFF_S + (grp * 64 + w4 * 16 + g) * 2;
                int s = 4 + grp, ph = 0;
#pragma unroll 1
                for (int it = 0; it < 16; it++) {
                    const uint32_t kb = sb + s * STAGE + koff;
                    mbar_wait(full0 + 8 * s, ph);
                    float sa[4] = {0.f, 0.f, 0.f, 0.f}, sc[4] = {0.f, 0.f, 0.f, 0.f};
                    uint32_t a[8][4];
#pragma unroll
                    for (int j = 0; j < 8; j++) ldsm4(a[j], kb ^ (j << 4));
#pragma unroll
                    for (int j = 0; j < 8; j += 2) {
                        mma16816(sa, a[j], qf[j][0], qf[j][1]);
                        mma16816(sc, a[j + 1], qf[j + 1][0], qf[j + 1][1]);
                    }
                    release_stage<2>(empty0 + 8 * s, lane);
                    uint32_t pk = pack_bf16(e ? sa[1] + sc[1] : sa[0] + sc[0], e ? sa[3] + sc[3] : sa[2] + sc[2]);
                    pk = pack_bf16(bf_lo(pk) * 0.08838834764831845f, bf_hi(pk) * 0.08838834764831845f);
                    if (diag) { sts_u16(sdst, pk); sts_u16(sdst + 16, pk >> 16); }
                    sdst += 256;
                    s += 2;
                    if (s >= NST) { s -= NST; ph ^= 1; }
                }
            }
            {
                __syncwarp();
                const int t = (lane & 30) + grp, hf = lane & 1;
                float sv[8];
                unpack8(lds_v4(sb + OFF_S + (t * 64 + w4 * 16 + hf * 8) * 2), sv);
                float m = -3.4028234663852886e38f;
#pragma unroll
                for (int i = 0; i < 8; i++) m = fmaxf(m, sv[i]);
                m = warp_max(m);
                float l = 0.f;
#pragma unroll
                for (int i = 0; i < 8; i++) { sv[i] = exp_diff(sv[i], m); l += sv[i]; }
                l = warp_sum(l);
                if (lane < 2) st_async_v2(mapa(sb + OFF_ML + (rank * 8 + warp) * 8, lane), m, l, mapa(mlbar, lane));
                mbar_wait_cluster(mlbar, 0);
                const float2 ml = lds_f32x2(sb + OFF_ML + (lane & 15) * 8);
                const float M = warp_max(ml.x);
                float L = exp_diff(ml.x, M) * ml.y;
#pragma unroll
                for (int ofs = 8; ofs > 0; ofs >>= 1) L += __shfl_xor_sync(0xffffffffu, L, ofs);
                const float f = __fdiv_rn(exp_diff(m, M), L);
#pragma unroll
                for (int j = 0; j < 4; j++) sts_u32(sb + OFF_P + t * 128 + j * 32 + w4 * 8 + hf * 4, pack_bf16(sv[2 * j] * f, sv[2 * j + 1] * f));
            }
            const uint32_t vbase = pin(sb + (8 * (mi >> 1) + r) * 256 + grp * 128 + ((2 * w4) ^ (mi & 1) ^ (r >> 2) ^ (2 * (r & 3) + grp)) * 16);
            const uint32_t wbase0 = pin(sb + (warp >> 1) * 4096 + (r + 8 * (mi >> 1)) * 128 + ((4 * (warp & 1) + (mi & 1)) ^ r) * 16);
            const uint32_t wbase1 = pin(wbase0 ^ 32);
            const uint32_t o_loc = pin(sb + OFF_OPART + rank * 512 + (warp * 8 + g) * 8);
            const uint32_t o_dst = pin(mapa(o_loc, rank ^ 1)), o_bar = pin(mapa(obar + c * 8, rank ^ 1));
            const uint32_t o_src = pin(sb + OFF_OPART + lane * 16), obar_p = pin(obar);
            const uint32_t first = pin((uint32_t)(c == 0)), cq = pin((uint32_t)c);
            const bool lane0 = pin((uint32_t)(lane == 0)), odd = pin((uint32_t)(c & 1));
            unsigned long long* const acc_p = pin(p.acc + acc_slot(b * DM + rank * 256 + tid));
            __nv_bfloat16* const out_p = pin(p.out + b * DM + rank * 256 + warp * 32 + c * 8 + g);
            const bool feed = pin((uint32_t)((c >> 1) == (g & 1))), low = pin((uint32_t)(c < 2));
            bar_sync(1, 256);
            float oc[4][4];
#pragma unroll
            for (int j = 0; j < 4; j++) { oc[j][0] = oc[j][1] = oc[j][2] = oc[j][3] = 0.f; }
            {
                auto pv_tile = [&](uint32_t vb, const uint4& p0, const uint4& p1) {
                    uint32_t a[4][4];
#pragma unroll
                    for (int j = 0; j < 4; j++) ldsm4t(a[j], vb + j * 4096);
                    mma16816(oc[0], a[0], p0.x, p0.y);
                    mma16816(oc[1], a[1], p0.z, p0.w);
                    mma16816(oc[2], a[2], p1.x, p1.y);
                    mma16816(oc[3], a[3], p1.z, p1.w);
                };
                uint32_t psrc = sb + OFF_P + c * 32;
                uint4 pe[EG][2];
#pragma unroll
                for (int j = 0; j < EG; j++) {
                    pe[j][0] = pe[j][1] = make_uint4(0u, 0u, 0u, 0u);
                    if (feed) { pe[j][0] = lds_v4(psrc + (32 - EG + j) * 128); pe[j][1] = lds_v4(psrc + (32 - EG + j) * 128 + 16); }
                }
                int s = 36 % NST, ph = (36 / NST) & 1;
#pragma unroll 1
                for (int it = 0; it < 32 - EG; it++) {
                    uint4 p0 = make_uint4(0u, 0u, 0u, 0u), p1 = p0;
                    if (feed) { p0 = lds_v4(psrc); p1 = lds_v4(psrc + 16); }
                    psrc += 128;
                    mbar_wait(full0 + 8 * s, ph);
                    pv_tile(vbase + s * STAGE, p0, p1);
                    if (it < 36 - NST) release_stage<1>(empty0 + 8 * s, lane);
                    if (++s == NST) { s = 0; ph ^= 1; }
                }
#pragma unroll
                for (int j = 0; j < EG; j++) {
                    mbar_wait(full0 + 8 * (NST - 4 - EG + j), (72 / NST - 1) & 1);
                    pv_tile(vbase + (NST - 4 - EG + j) * STAGE, pe[j][0], pe[j][1]);
                }
            }
            asm volatile("{\n.reg .pred p;\nsetp.ne.u32 p, %5, 0;\n"
                         "@p st.async.shared::cluster.mbarrier::complete_tx::bytes.v2.f32 [%0], {%1, %2}, [%3];\n"
                         "@p st.shared.v2.f32 [%4], {%1, %2};\n}"
                         ::"r"(o_dst),
                           "f"((((oc[0][0] + oc[0][3]) + (oc[1][0] + oc[1][3])) + (oc[2][0] + oc[2][3])) + (oc[3][0] + oc[3][3])),
                           "f"((((oc[0][1] + oc[0][2]) + (oc[1][1] + oc[1][2])) + (oc[2][1] + oc[2][2])) + (oc[3][1] + oc[3][2])),
                           "r"(o_bar), "r"(o_loc), "r"(first) : "memory");
            __syncwarp();
            if (lane0) mbar_arrive<1>(obar_p);
            mbar_wait_cluster(obar_p, 0);
            uint32_t of[8][2];
            {
                const uint4 u = lds_v4(o_src), v = lds_v4(o_src + 512);
                const uint32_t f0 = pack_bf16(__uint_as_float(u.x) + __uint_as_float(v.x), __uint_as_float(u.z) + __uint_as_float(v.z));
                const uint32_t f1 = pack_bf16(__uint_as_float(u.y) + __uint_as_float(v.y), __uint_as_float(u.w) + __uint_as_float(v.w));
#pragma unroll
                for (int t = 0; t < 8; t++) {
                    of[t][0] = __shfl_sync(0xffffffffu, f0, 4 * t + cq);
                    of[t][1] = __shfl_sync(0xffffffffu, f1, 4 * t + cq);
                }
            }
            float y0[4] = {0.f, 0.f, 0.f, 0.f}, y1[4] = {0.f, 0.f, 0.f, 0.f};
#pragma unroll
            for (int t = 0; t < 4; t++) {
                uint32_t a[4][4];
                mbar_wait(full0 + 8 * (NST - 4 + t), (72 / NST - 1) & 1);
#pragma unroll
                for (int j = 0; j < 4; j++) ldsm4t(a[j], ((j & 1) ? wbase1 : wbase0) + (NST - 4 + t) * STAGE + (j >> 1) * 2048);
                mma16816(y0, a[0], of[2 * t][0], of[2 * t][1]);
                mma16816(y1, a[1], of[2 * t][0], of[2 * t][1]);
                mma16816(y0, a[2], of[2 * t + 1][0], of[2 * t + 1][1]);
                mma16816(y1, a[3], of[2 * t + 1][0], of[2 * t + 1][1]);
            }
            const float z0 = odd ? y0[2] : y0[0], z1 = odd ? y1[2] : y1[0];
            contribute(acc_p, out_p, low ? z0 : z1, needs_float_path((fabsf(y0[0]) + fabsf(y0[2])) + (fabsf(y1[0]) + fabsf(y1[2]))));
        }
    } else {
        const int fj = cta - NATT;
        const int sh1 = fj & 1;
        const int T1 = 32 + sh1, T2 = (fj == NFFN - 1) ? (FF - (NFFN - 1) * FSL) / 16 : FSL / 16;
        uint4 xs0, xs1;
        uint32_t bias_raw[6], res_raw[6];
        if (warp < 8) {
            xs0 = ldg_v4(p.x + (warp & 1) * DM + lane * 16);
            xs1 = ldg_v4(p.x + (warp & 1) * DM + lane * 16 + 8);
#pragma unroll
            for (int j = 0; j < 6; j++) bias_raw[j] = ldg_u16(p.b1 + min(fj * FSL + (warp + 8 * (j >> 1)) * 16 + (j & 1) * 8 + g, FF - 1));
#pragma unroll
            for (int j = 0; j < 6; j++) res_raw[j] = ldg_u16((j < 4 ? p.x + (j >> 1) * DM : p.b2) + warp * 64 + c * 16 + (j & 1) * 8 + g);
        } else if (lane == 0) {
            prefetch_map(&maps.w1);
#pragma unroll
            for (int s = 0; s < NST; s++) { mbar_init(full0 + 8 * s, 1); mbar_init(empty0 + 8 * s, 8); }
            mbar_init_fence();
        }
        __syncthreads();
        if (warp == 8) {
            if (lane == 0) {
                const char* p2 = (const char*)(p.w2 + (size_t)fj * FSL * DM);
                const uint64_t pol = policy_evict_first();
                int s = 0, ph = 1;
#pragma unroll 1
                for (int i = 0; i < T1 + T2 + NST; i++) {
                    mbar_wait_bounded(empty0 + 8 * s, ph);
                    if (i < T1) {
                        mbar_expect_tx(full0 + 8 * s, 16 * FSL * 2);
                        tensor_load(sb + s * STAGE, &maps.w1, fj * (FSL / 2), i * 16 - sh1, full0 + 8 * s, pol);
                    } else if (i < T1 + T2) {
                        mbar_expect_tx(full0 + 8 * s, STAGE);
                        bulk_load(sb + s * STAGE, p2 + (size_t)(i - T1) * STAGE, STAGE, full0 + 8 * s, pol);
                    }
                    if (++s == NST) { s = 0; ph ^= 1; }
                }
            }
        } else {
            const uint32_t xn_s = sb + OFF_QPART;
            const uint32_t g_s = xn_s + 2 * 1056;
            if (warp < 2) {
                float mean_bf, sd_bf, xn[16];
                ln_stats(xs0, xs1, mean_bf, sd_bf);
                unpack8(xs0, xn); unpack8(xs1, xn + 8);
#pragma unroll
                for (int i = 0; i < 16; i++) sts_u16(xn_s + warp * 1056 + (lane * 16 + i + sh1) * 2, pack_bf16(ln_apply(xn[i], mean_bf, sd_bf), 0.f));
                if (lane < 16) sts_u16(xn_s + warp * 1056 + (lane == 15 && sh1 ? 0 : DM + sh1 + lane) * 2, 0);
            }
            bar_sync(1, 256);
            int s = 0, ph = 0;
            float hacc[3][4];
#pragma unroll
            for (int j = 0; j < 3; j++) { hacc[j][0] = hacc[j][1] = hacc[j][2] = hacc[j][3] = 0.f; }
            uint32_t aoff[3];
#pragma unroll
            for (int j = 0; j < 3; j++) aoff[j] = (r + 8 * (mi >> 1)) * (FSL * 2) + min(2 * (warp + 8 * j) + (mi & 1), FSL / 8 - 1) * 16;
#pragma unroll 1
            for (int i = 0; i < T1; i++) {
                uint32_t f0 = 0, f1 = 0;
                if (g < 2) { f0 = lds_u32(xn_s + g * 1056 + i * 32 + c * 4); f1 = lds_u32(xn_s + g * 1056 + i * 32 + 16 + c * 4); }
                mbar_wait(full0 + 8 * s, ph);
#pragma unroll
                for (int j = 0; j < 3; j++) {
                    uint32_t a[4];
                    ldsm4t(a, sb + s * STAGE + aoff[j]);
                    mma16816(hacc[j], a, f0, f1);
                }
                release_stage<1>(empty0 + 8 * s, lane);
                if (++s == NST) { s = 0; ph ^= 1; }
            }
            if (c == 0) {
#pragma unroll
                for (int j = 0; j < 3; j++)
#pragma unroll
                    for (int hf = 0; hf < 2; hf++) {
                        const int f = (warp + 8 * j) * 16 + hf * 8 + g;
                        if (f < FSL) {
                            const float bias = bf_lo(bias_raw[2 * j + hf]);
#pragma unroll
                            for (int bb = 0; bb < 2; bb++) {
                                const float hv = rbf(rbf(hacc[j][2 * hf + bb]) + bias);
                                const float inner = 0.7978845608028654f * (hv + 0.044715f * hv * hv * hv);
                                sts_u16(g_s + bb * 704 + f * 2, pack_bf16(0.5f * hv * (1.f + tanhf(inner)), 0.f));
                            }
                        }
                    }
            }
            bar_sync(1, 256);
            float y[2][4][4];
#pragma unroll
            for (int bb = 0; bb < 2; bb++)
#pragma unroll
                for (int j = 0; j < 4; j++) { y[bb][j][0] = y[bb][j][1] = y[bb][j][2] = y[bb][j][3] = 0.f; }
            const int sh = (g & 1) * 16;
#pragma unroll 1
            for (int i = 0; i < T2; i++) {
                uint32_t f[2][2] = {{0u, 0u}, {0u, 0u}};
                if (diag) {
#pragma unroll
                    for (int bb = 0; bb < 2; bb++) {
                        f[bb][0] = lds_u16(g_s + bb * 704 + (i * 16 + g) * 2) << sh;
                        f[bb][1] = lds_u16(g_s + bb * 704 + (i * 16 + 8 + g) * 2) << sh;
                    }
                }
                const uint32_t wb = sb + s * STAGE + (r + 8 * (mi >> 1)) * 1024 + warp * 128 + (((mi & 1) * 4) ^ r) * 16;
                mbar_wait(full0 + 8 * s, ph);
#pragma unroll
                for (int j = 0; j < 4; j++) {
                    uint32_t a[4];
                    ldsm4t(a, wb ^ (j << 4));
                    mma16816(y[0][j], a, f[0][0], f[0][1]);
                    mma16816(y[1][j], a, f[1][0], f[1][1]);
                }
                release_stage<1>(empty0 + 8 * s, lane);
                if (++s == NST) { s = 0; ph ^= 1; }
            }
#pragma unroll
            for (int bb = 0; bb < 2; bb++) {
                float yy[16];
#pragma unroll
                for (int j = 0; j < 4; j++) { yy[2 * j] = y[bb][j][0]; yy[2 * j + 1] = y[bb][j][1]; yy[8 + 2 * j] = y[bb][j][2]; yy[8 + 2 * j + 1] = y[bb][j][3]; }
                float2 yo = fold8(yy);
                if (fj == 0) {
                    yo.x += bf_lo(res_raw[2 * bb]) + bf_lo(res_raw[4]);
                    yo.y += bf_lo(res_raw[2 * bb + 1]) + bf_lo(res_raw[5]);
                }
                const int n0 = bb * DM + warp * 64 + c * 16;
                unsigned long long* a = p.acc + acc_slot((n0 & ~31) + 4 * g + 2 * (c & 1));
                const bool fp = needs_float_path(warp_max(fabsf(yo.x) + fabsf(yo.y)));
                contribute(a, p.out + n0 + g, yo.x, fp);
                contribute(a + 1, p.out + n0 + 8 + g, yo.y, fp);
            }
        }
    }
}

typedef CUresult (*EncodeFn)(CUtensorMap*, CUtensorMapDataType, cuuint32_t, void*, const cuuint64_t*, const cuuint64_t*,
                             const cuuint32_t*, const cuuint32_t*, CUtensorMapInterleave, CUtensorMapSwizzle,
                             CUtensorMapL2promotion, CUtensorMapFloatOOBfill);

void encode_2d(EncodeFn fn, CUtensorMap* map, CUtensorMapDataType dt, const void* base, uint64_t cols, uint64_t rows,
               uint64_t pitch_bytes, uint32_t box_cols, uint32_t box_rows, CUtensorMapSwizzle sw) {
    const cuuint64_t dims[2] = {cols, rows}, strides[1] = {pitch_bytes};
    const cuuint32_t box[2] = {box_cols, box_rows}, estr[2] = {1, 1};
    fn(map, dt, 2, const_cast<void*>(base), dims, strides, box, estr, CU_TENSOR_MAP_INTERLEAVE_NONE, sw,
       CU_TENSOR_MAP_L2_PROMOTION_NONE, CU_TENSOR_MAP_FLOAT_OOB_FILL_NONE);
}

}

extern "C" void kernel_launch(void* const* d_in, const int* in_sizes, int n_in, void* d_out, int out_size) {
    (void)in_sizes; (void)n_in; (void)out_size;
    typedef const __nv_bfloat16* P;
    static EncodeFn encode = nullptr;
    static void* acc = nullptr;
    static double stream_ns = 0.0;
    if (!encode) {
        cudaFuncSetAttribute(fused_decode_kernel, cudaFuncAttributeMaxDynamicSharedMemorySize, SMEM_BYTES);
        cudaDriverEntryPointQueryResult st;
        cudaGetDriverEntryPoint("cuTensorMapEncodeTiled", (void**)&encode, cudaEnableDefault, &st);
        cudaGetSymbolAddress(&acc, g_acc);
        int dev = 0, sms = 0, khz = 0, bits = 0;
        cudaGetDevice(&dev);
        cudaDeviceGetAttribute(&sms, cudaDevAttrMultiProcessorCount, dev);
        cudaDeviceGetAttribute(&khz, cudaDevAttrMemoryClockRate, dev);
        cudaDeviceGetAttribute(&bits, cudaDevAttrGlobalMemoryBusWidth, dev);
        const double bytes = 2.0 * (2.0 * 2 * NH * WIN * DH + 2.0 * DM * NH * DH + 2.0 * DM * FF);
        if (sms >= NCTA && khz > 0 && bits > 0) stream_ns = bytes / (2.0 * khz * 1e-6 * bits / 8);
    }
    Params p;
    p.kc = (P)d_in[1]; p.x = (P)d_in[0];
    p.acc = (unsigned long long*)acc; p.out = (__nv_bfloat16*)d_out;
    p.w2 = (P)d_in[8]; p.b1 = (P)d_in[7]; p.b2 = (P)d_in[9];
    p.t_end = (int)(stream_ns * 1.0111);
    p.t_tile = (int)(stream_ns / 64.3);
    Maps maps;
    encode_2d(encode, &maps.wq, CU_TENSOR_MAP_DATA_TYPE_BFLOAT16, d_in[3], NH * DH, DM, NH * DH * 2, DH, 64,
              CU_TENSOR_MAP_SWIZZLE_NONE);
    encode_2d(encode, &maps.v, CU_TENSOR_MAP_DATA_TYPE_BFLOAT16, d_in[2], 64, (uint64_t)2 * 2 * NH * SK, 128, 64, 128,
              CU_TENSOR_MAP_SWIZZLE_128B);
    {
        const cuuint64_t dims[3] = {64, NH * DH, DM / 64}, strides[2] = {DM * 2, 128};
        const cuuint32_t box[3] = {64, 32, 4}, estr[3] = {1, 1, 1};
        encode(&maps.wo, CU_TENSOR_MAP_DATA_TYPE_BFLOAT16, 3, d_in[4], dims, strides, box, estr, CU_TENSOR_MAP_INTERLEAVE_NONE,
               CU_TENSOR_MAP_SWIZZLE_128B, CU_TENSOR_MAP_L2_PROMOTION_NONE, CU_TENSOR_MAP_FLOAT_OOB_FILL_NONE);
    }
    encode_2d(encode, &maps.w1, CU_TENSOR_MAP_DATA_TYPE_UINT32, d_in[6], FF / 2, DM, FF * 2, FSL / 2, 16,
              CU_TENSOR_MAP_SWIZZLE_NONE);
    fused_decode_kernel<<<NCTA, NTHREADS, SMEM_BYTES>>>(p, maps);
}
```
